```python
import torch

def _softmax(x, axis=-1):
    return torch.softmax(x, dim=axis)
def _gelu(x):
    return torch.nn.functional.gelu(x, approximate="tanh")
def _silu(x):
    return torch.nn.functional.silu(x)
def _sigmoid(x):
    return torch.sigmoid(x)
def _layernorm(x, axis=-1, eps=1e-5):
    m = x.mean(dim=axis, keepdim=True)
    v = x.var(dim=axis, keepdim=True, unbiased=False)
    return (x - m) / torch.sqrt(v + eps)
def _scatter_add(tgt, idx, src, axis=0):
    return tgt.clone().index_add_(axis, idx, src)
def _segment_sum(src, seg, n):
    out = torch.zeros((n,) + src.shape[1:], dtype=src.dtype)
    return out.index_add_(0, seg, src)
def _pad(x, pw):
    flat = tuple(v for pair in reversed(pw) for v in pair)
    return torch.nn.functional.pad(x, flat)

kernel_name = 'gated_mix__compressed_kv_cla__dense_activation_silu__decode'

def setup_inputs():

    _w = (lambda a: (lambda t: t.to(torch.bfloat16) if t.is_floating_point() else t)(torch.as_tensor(a)))
    def _A_setup():
        B, H, Sq, Sk, D, M = 1, 32, 1, 4096, 128, 640
        Dc = 4 * D
        return {
            "x": _w((lambda *s: torch.randn(*s, dtype=torch.bfloat16) * 0.05)(B, Sq, M)),
            "c_kv": _w((lambda *s: torch.randn(*s, dtype=torch.bfloat16) * 0.2)(B, Sk, Dc)),
            "w_q": _w((lambda *s: torch.randn(*s, dtype=torch.bfloat16) * 3.2)(M, H, D) * (M ** -0.5)),
            "w_uk": _w((lambda *s: torch.randn(*s, dtype=torch.bfloat16) * 3.2)(Dc, H, D) * (Dc ** -0.5)),
            "w_uv": _w((lambda *s: torch.randn(*s, dtype=torch.bfloat16) * 0.2)(Dc, H, D) * (Dc ** -0.5)),
            "w_o": _w((lambda *s: torch.randn(*s, dtype=torch.bfloat16) * 0.2)(H, D, M) * ((H * D) ** -0.5)),
        }
    _A_in = _A_setup()

    def _B_setup():
        B, S, D, F = 1, 1, 640, 1728
        return {
            "x": _w((lambda *s: torch.randn(*s, dtype=torch.bfloat16) * 0.05)(B, S, D)),
            "w1": _w((lambda *s: torch.randn(*s, dtype=torch.bfloat16) * 0.05)(D, F) * (D ** -0.5)),
            "w2": _w((lambda *s: torch.randn(*s, dtype=torch.bfloat16) * 0.05)(F, D) * (F ** -0.5)),
        }
    _B_in = _B_setup()

    return {
        "A_x": _A_in["x"],
        "A_c_kv": _A_in["c_kv"],
        "A_w_q": _A_in["w_q"],
        "A_w_uk": _A_in["w_uk"],
        "A_w_uv": _A_in["w_uv"],
        "A_w_o": _A_in["w_o"],
        "B_x": _B_in["x"],
        "B_w1": _B_in["w1"],
        "B_w2": _B_in["w2"],
        "gate_w": _w((lambda *s: torch.randn(*s, dtype=torch.bfloat16) * 0.05)(640) * 16.0),
    }

def reference(A_x, A_c_kv, A_w_q, A_w_uk, A_w_uv, A_w_o, B_x, B_w1, B_w2, gate_w):
    def _A_ref(x, c_kv, w_q, w_uk, w_uv, w_o):
        B, Sq, M = x.shape[0], x.shape[1], x.shape[2]
        Sk = c_kv.shape[1]
        H, D = w_q.shape[1], w_q.shape[2]
        q = torch.einsum("bqm,mhd->bhqd", x, w_q)
        k = torch.einsum("bkc,chd->bhkd", c_kv, w_uk)
        v = torch.einsum("bkc,chd->bhkd", c_kv, w_uv)
        scores = torch.einsum("bhqd,bhkd->bhqk", q, k) * (D ** -0.5)
        off = Sk - Sq
        qi = torch.arange(Sq)[:, None]
        kj = torch.arange(Sk)[None, :]
        cmask = kj <= (qi + off)
        scores = torch.where(cmask[None, None], scores, -1e9)
        p = _softmax(scores, axis=-1)
        ctx = torch.einsum("bhqk,bhkd->bhqd", p, v)
        return torch.einsum("bhqd,hdm->bqm", ctx, w_o)

    def _B_ref(x, w1, w2):
        h = torch.einsum("bsd,df->bsf", x, w1)
        h = _silu(h)
        out = torch.einsum("bsf,fd->bsd", h, w2)
        return out

    x = A_x
    g = _sigmoid((x * gate_w).sum(-1, keepdims=True))
    a = _A_ref(x, A_c_kv, A_w_q, A_w_uk, A_w_uv, A_w_o)
    b = _B_ref(x, B_w1, B_w2)
    return g * a + (1 - g) * b
```

```cpp
#include <cuda_runtime.h>
#include <cuda_bf16.h>
#include <cuda.h>
#include <stdint.h>
#include <stdlib.h>

namespace {

typedef unsigned long long u64;
constexpr int MD = 640, DC = 512, SK = 4096, FF = 1728;
constexpr int NCTA = 128;
constexpr int NCOMP = 512;
constexpr int NTHREADS = NCOMP + 128;
constexpr int SPIN_MAX = 1 << 20;

struct Tune { int DD, DD1, TA1, DA1, T3, DP2, DA2, NP2, DP3, TQ0, TQ, TS, LB, LB1, PH, V1, V2, S1, S2, S3, OFF; };
#define TV(n, d) (d)
static Tune tune() {
    Tune t;
    t.DD = TV(DD, 168);
    t.DD1 = TV(DD1, 174);
    t.TA1 = TV(TA1, 2900);
    t.DA1 = TV(DA1, 176);
    t.T3 = TV(T3, 4280);
    t.DP2 = TV(DP2, t.DD * 3 / 2);
    t.DA2 = TV(DA2, 410);
    t.NP2 = TV(NP2, 16);
    t.DP3 = TV(DP3, t.DD);
    t.TQ = TV(TQ, 4700);
    t.TS = TV(TS, 6850);
    t.LB = TV(LB, 1600);
    t.LB1 = TV(LB1, 0);
    t.TQ0 = TV(TQ0, 4450);
    t.PH = TV(PH, 200);
    t.V1 = TV(V1, 2000); t.V2 = TV(V2, 3200); t.S1 = TV(S1, 100); t.S2 = TV(S2, 106); t.S3 = TV(S3, 100);
    t.OFF = TV(OFF, 0);
    t.TQ += t.OFF; t.TQ0 += t.OFF; t.TS += t.OFF;
    return t;
}
#define CAP 16
#define PREW 0
#define FAST 1
#define TWO 1
#define PRE 1
#define FIN2 0
#define ROLEMIX 1

constexpr int OFF_WUK = 0, OFF_WUV = 65536, OFF_WO = 131072;
constexpr int OFF_C = 0, OFF_W1 = 65536, OFF_W2 = OFF_W1 + 40960;
constexpr int OFF_Q = OFF_W2 + 40960, OFF_P = OFF_Q + 16384, OFF_SREM = OFF_P + 8192, OFF_OT = OFF_SREM + 8192;
constexpr int OFF_XS = 212992;
constexpr int OFF_EX0 = OFF_XS + 2560;
constexpr int OFF_EX1 = OFF_EX0 + 1024;
constexpr int OFF_O = OFF_EX1 + 1024;
constexpr int OFF_SMAX = OFF_O + 4224;
constexpr int OFF_LSUM = OFF_SMAX + 256;
constexpr int OFF_TL = OFF_LSUM + 1024;
constexpr int OFF_BAR = OFF_TL + 256;
enum { B_X = 0, B_EX0 = 1, B_EX1 = 2, B_EX2 = 3, B_T = 4, B_COUNT = B_T + 36 };
constexpr int SMEM_BYTES = OFF_BAR + B_COUNT * 8 + 1024;
static_assert(SMEM_BYTES <= 232448, "smem");
enum { P_WQ = 0, P_WUK = 10, P_WUV = 18, P_WO = 26, P_END = 36, A_C = 0, A_W1 = 8, A_W2 = 13, A_END = 23 };

struct Scratch {
    u64 x1[64][64];
    u64 x4[40][128][8];
    u64 x2[64][32][64];
    u64 st[64][32][8];
    u64 sig[64][32][4];
    unsigned int epoch;
};
__device__ Scratch g_scr;

struct Params {
    const __nv_bfloat16* x;
    const __nv_bfloat16* gw;
    __nv_bfloat16* out;
    Scratch* scr;
    int tq0, tq, ts, lb, lb1, ph;
    uint4 tile[2][36];
    CUtensorMap m[7];
};

#define TLT(i, th)

__device__ __forceinline__ uint32_t s_u32(const void* p) { return (uint32_t)__cvta_generic_to_shared(p); }
__device__ __forceinline__ float bf_lo(uint32_t w) { return __uint_as_float(w << 16); }
__device__ __forceinline__ float bf_hi(uint32_t w) { return __uint_as_float(w & 0xffff0000u); }
__device__ __forceinline__ float bf_round(float v) { return __bfloat162float(__float2bfloat16_rn(v)); }
__device__ __forceinline__ uint32_t pack_bf(float lo, float hi) {
    uint32_t r; asm("cvt.rn.bf16x2.f32 %0, %1, %2;" : "=r"(r) : "f"(hi), "f"(lo)); return r;
}
__device__ __forceinline__ float ex2(float v) { float r; asm("ex2.approx.ftz.f32 %0, %1;" : "=f"(r) : "f"(v)); return r; }
__device__ __forceinline__ uint32_t tag_word(uint32_t w, uint32_t tag) { return (w & ~1u) | tag; }
__device__ __forceinline__ void pin(uint32_t v) { asm volatile("{.reg .pred p; setp.eq.u32 p, %0, 0xfffffff1; @p st.shared.u32 [%0], %0;}" :: "r"(v) : "memory"); }
__device__ __forceinline__ void pin(const void* v) { asm volatile("{.reg .pred p; setp.eq.u64 p, %0, 1; @p st.global.u32 [%0], 0;}" :: "l"(v) : "memory"); }
__device__ __forceinline__ uint32_t lds32(uint32_t a) { uint32_t v; asm volatile("ld.shared.u32 %0, [%1];" : "=r"(v) : "r"(a) : "memory"); return v; }
__device__ __forceinline__ float ldsf(uint32_t a) { return __uint_as_float(lds32(a)); }
__device__ __forceinline__ uint2 lds64(uint32_t a) { uint2 v; asm volatile("ld.shared.v2.u32 {%0,%1}, [%2];" : "=r"(v.x), "=r"(v.y) : "r"(a) : "memory"); return v; }
__device__ __forceinline__ uint4 lds128(uint32_t a) {
    uint4 v; asm volatile("ld.shared.v4.u32 {%0,%1,%2,%3}, [%4];" : "=r"(v.x), "=r"(v.y), "=r"(v.z), "=r"(v.w) : "r"(a) : "memory"); return v;
}
__device__ __forceinline__ void sts32(uint32_t a, uint32_t v) { asm volatile("st.shared.u32 [%0], %1;" :: "r"(a), "r"(v) : "memory"); }
__device__ __forceinline__ void sts64(uint32_t a, uint32_t x, uint32_t y) { asm volatile("st.shared.v2.u32 [%0], {%1,%2};" :: "r"(a), "r"(x), "r"(y) : "memory"); }
__device__ __forceinline__ void sts128(uint32_t a, const uint4& v) {
    asm volatile("st.shared.v4.u32 [%0], {%1,%2,%3,%4};" :: "r"(a), "r"(v.x), "r"(v.y), "r"(v.z), "r"(v.w) : "memory");
}
#define F(x) __uint_as_float(x)

__device__ __forceinline__ void st_pkt(u64* p, uint32_t lo, uint32_t hi) {
    asm volatile("{.reg .b64 v; mov.b64 v, {%1,%2}; st.relaxed.gpu.global.b64 [%0], v;}" :: "l"(p), "r"(lo), "r"(hi) : "memory");
}
__device__ __forceinline__ uint2 ld_pkt(const u64* p) {
    uint2 v; asm volatile("{.reg .b64 v; ld.relaxed.gpu.global.b64 v, [%2]; mov.b64 {%0,%1}, v;}" : "=r"(v.x), "=r"(v.y) : "l"(p) : "memory"); return v;
}
__device__ __forceinline__ uint4 ld_pkt2(const u64* p) {
    uint4 v; asm volatile("{.reg .b64 a,b; ld.relaxed.gpu.global.v2.b64 {a,b}, [%4]; mov.b64 {%0,%1}, a; mov.b64 {%2,%3}, b;}"
                          : "=r"(v.x), "=r"(v.y), "=r"(v.z), "=r"(v.w) : "l"(p) : "memory"); return v;
}
__device__ __forceinline__ bool fresh2(const uint4& v, uint32_t tag) { return (((v.x ^ tag) | (v.z ^ tag)) & 1u) == 0; }
__device__ __forceinline__ uint32_t now_ns() { uint32_t v; asm volatile("mov.u32 %0, %%globaltimer_lo;" : "=r"(v)); return v; }
__device__ __forceinline__ void wait_until(uint32_t t0, int when) {
    while ((int)(now_ns() - t0) < when - 400) __nanosleep(100);
    while ((int)(now_ns() - t0) < when) { }
}

__device__ __forceinline__ void mbar_wait(uint32_t bar) {
    asm volatile("{\n.reg .pred p;\nLW:\nmbarrier.try_wait.parity.shared::cta.b64 p, [%0], 0;\n@!p bra.uni LW;\n}" :: "r"(bar) : "memory");
}
__device__ __forceinline__ void mbar_wait2(uint32_t bar0, uint32_t bar1) {
    asm volatile("{\n.reg .pred p, q;\nLW:\nmbarrier.try_wait.parity.shared::cta.b64 p, [%0], 0;\n"
                 "mbarrier.try_wait.parity.shared::cta.b64 q, [%1], 0;\nand.pred p, p, q;\n@!p bra.uni LW;\n}" :: "r"(bar0), "r"(bar1) : "memory");
}
__device__ __forceinline__ void expect_tx(uint32_t bar, uint32_t bytes) {
    asm volatile("mbarrier.arrive.expect_tx.relaxed.cta.shared::cta.b64 _, [%0], %1;" :: "r"(bar), "r"(bytes) : "memory");
}
__device__ __forceinline__ void tma2d(uint32_t dst, u64 map, uint32_t c0, uint32_t c1, uint32_t bar) {
    asm volatile("cp.async.bulk.tensor.2d.shared::cluster.global.mbarrier::complete_tx::bytes [%0], [%1, {%2, %3}], [%4];"
                 :: "r"(dst), "l"(map), "r"(c0), "r"(c1), "r"(bar) : "memory");
}
__device__ __forceinline__ void bar_sync(int id, int n) { asm volatile("bar.sync %0, %1;" :: "r"(id), "r"(n) : "memory"); }
__device__ __forceinline__ uint32_t peer_addr(uint32_t a, uint32_t rank) {
    uint32_t r; asm("mapa.shared::cluster.u32 %0, %1, %2;" : "=r"(r) : "r"(a), "r"(rank)); return r;
}
__device__ __forceinline__ void st_async1(uint32_t dst, float a, uint32_t bar) {
    asm volatile("st.async.shared::cluster.mbarrier::complete_tx::bytes.f32 [%0], %1, [%2];" :: "r"(dst), "f"(a), "r"(bar) : "memory");
}
__device__ __forceinline__ void ldsm4(uint32_t* r, uint32_t a) {
    asm volatile("ldmatrix.sync.aligned.m8n8.x4.shared.b16 {%0,%1,%2,%3}, [%4];"
                 : "=r"(r[0]), "=r"(r[1]), "=r"(r[2]), "=r"(r[3]) : "r"(a) : "memory");
}
__device__ __forceinline__ void ldsm4t(uint32_t* r, uint32_t a) {
    asm volatile("ldmatrix.sync.aligned.m8n8.x4.trans.shared.b16 {%0,%1,%2,%3}, [%4];"
                 : "=r"(r[0]), "=r"(r[1]), "=r"(r[2]), "=r"(r[3]) : "r"(a) : "memory");
}
__device__ __forceinline__ void mma_w(float* c, const uint32_t* a, uint32_t b0, uint32_t b1) {
    asm volatile("mma.sync.aligned.m16n8k16.row.col.f32.bf16.bf16.f32 {%0,%1,%2,%3}, {%4,%5,%6,%7}, {%8,%9}, {%0,%1,%2,%3};"
                 : "+f"(c[0]), "+f"(c[1]), "+f"(c[2]), "+f"(c[3]) : "r"(a[0]), "r"(a[1]), "r"(a[2]), "r"(a[3]), "r"(b0), "r"(b1));
}
#define WG_D "{%0,%1,%2,%3,%4,%5,%6,%7,%8,%9,%10,%11,%12,%13,%14,%15}"
#define WG_DREGS "+f"(d[0]), "+f"(d[1]), "+f"(d[2]), "+f"(d[3]), "+f"(d[4]), "+f"(d[5]), "+f"(d[6]), "+f"(d[7]), \
                 "+f"(d[8]), "+f"(d[9]), "+f"(d[10]), "+f"(d[11]), "+f"(d[12]), "+f"(d[13]), "+f"(d[14]), "+f"(d[15])
__device__ __forceinline__ void wgmma_rs(float* d, const uint32_t* a, u64 desc) {
    asm volatile("wgmma.mma_async.sync.aligned.m64n32k16.f32.bf16.bf16 " WG_D ", {%16,%17,%18,%19}, %20, 1, 1, 1, 0;"
                 : WG_DREGS : "r"(a[0]), "r"(a[1]), "r"(a[2]), "r"(a[3]), "l"(desc) : "memory");
}
__device__ __forceinline__ void wgmma_ss(float* d, u64 adesc, u64 desc) {
    asm volatile("wgmma.mma_async.sync.aligned.m64n32k16.f32.bf16.bf16 " WG_D ", %16, %17, 1, 1, 1, 0, 0;"
                 : WG_DREGS : "l"(adesc), "l"(desc) : "memory");
}
__device__ __forceinline__ void zero16(float* d) {
#pragma unroll
    for (int i = 0; i < 16; ++i) { d[i] = 0.f; asm volatile("" : "+f"(d[i])); }
}
__device__ __forceinline__ void stsm4t(uint32_t a, const uint32_t* r) {
    asm volatile("stmatrix.sync.aligned.m8n8.x4.trans.shared.b16 [%0], {%1,%2,%3,%4};" :: "r"(a), "r"(r[0]), "r"(r[1]), "r"(r[2]), "r"(r[3]) : "memory");
}
__device__ __forceinline__ void st_pkt2(u64* p, const uint4& v) {
    asm volatile("{.reg .b64 a,b; mov.b64 a, {%1,%2}; mov.b64 b, {%3,%4}; st.relaxed.gpu.global.v2.b64 [%0], {a,b};}"
                 :: "l"(p), "r"(v.x), "r"(v.y), "r"(v.z), "r"(v.w) : "memory");
}
__device__ __forceinline__ u64 sdesc(uint32_t addr) {
    return (u64)((addr & 0x3FFFFu) >> 4) | (1ull << 16) | (64ull << 32) | (1ull << 62);
}
__device__ __forceinline__ float shx(float v, int m) { return __shfl_xor_sync(0xffffffffu, v, m); }

constexpr int BAR_ALL = 1, BAR_HALF = 2, BAR_L = 4, BAR_WG = 5, BAR_Q = 9;
__device__ __forceinline__ void spin(uint32_t n) { const uint32_t c = clock(); while ((uint32_t)clock() - c < n) { } }
__device__ __forceinline__ int f2ord(int b) { return b ^ ((b >> 31) & 0x7fffffff); }

__global__ void __cluster_dims__(2, 1, 1) __launch_bounds__(NTHREADS, 1)
fused_kernel(const __nv_bfloat16* __restrict__ wq, const __grid_constant__ Params prm) {
    extern __shared__ __align__(1024) unsigned char sm_raw[];
    uint32_t sbase = (s_u32(sm_raw) + 1023u) & ~1023u;
    asm volatile("" : "+r"(sbase));
    const uint32_t t0 = now_ns();
    const int t = threadIdx.x, lane = t & 31;
    {
        const uint32_t b = blockIdx.x, ut = threadIdx.x;
        const uint32_t off = (320 * (b & 1) + ((ut >> 2) & 64) + ((ut >> 3) & 15)) * 8192 + (b >> 2) * 256 + (ut & 128) + (ut & 7) * 16;
        const char* src = reinterpret_cast<const char*>(wq) + off;
        const uint32_t dst = sbase + OFF_WO + (ut >> 7) * 8192 + (ut & 120) * 16 + (((ut ^ (ut >> 3)) & 7) << 4);
        const uint32_t skip = (ut >> 9) | (((b >> 1) ^ (ROLEMIX ? b >> 4 : 0)) & 1);
        asm volatile("{.reg .pred p; setp.eq.u32 p, %2, 0;\n"
                     "@p cp.async.cg.shared.global [%0], [%1], 16;\n"
                     "@p cp.async.cg.shared.global [%0+2048], [%1+131072], 16;\n"
                     "@p cp.async.cg.shared.global [%0+4096], [%1+262144], 16;\n"
                     "@p cp.async.cg.shared.global [%0+6144], [%1+393216], 16;}"
                     :: "r"(dst), "l"(src), "r"(skip) : "memory");
    }
    const int wb = __shfl_sync(0xffffffffu, (t >> 5) | (blockIdx.x << 8), 0);
    const int warp = wb & 255, r = (wb >> 8) & 1, id = wb >> 10, me = 2 * id + r;
    const bool roleA = ((wb >> 9) ^ (ROLEMIX ? wb >> 12 : 0)) & 1;
    const bool ffn = id < 27;
    const uint32_t bars = sbase + OFF_BAR, tb = bars + 8 * B_T;

    if (warp >= 16) {
        const int k = warp - 16;
        const u64 mapbase = reinterpret_cast<u64>(&prm.m[0]);
        if (lane == 0) {
            asm volatile("prefetch.tensormap [%0];" :: "l"(mapbase + 128 * (roleA ? 3 + k : k)) : "memory");
            asm volatile("mbarrier.init.shared::cta.b64 [%0], %1;" :: "r"(tb + 8 * k), "r"(roleA ? 1 : 128) : "memory");
            if (k == 0) {
                asm volatile("mbarrier.init.shared::cta.b64 [%0], 1;" :: "r"(bars + 8 * B_X) : "memory");
                expect_tx(bars + 8 * B_X, roleA ? 2560 : 1280);
                asm volatile("cp.async.bulk.shared::cluster.global.mbarrier::complete_tx::bytes [%0], [%1], 1280, [%2];"
                             :: "r"(sbase + OFF_XS), "l"(prm.x), "r"(bars + 8 * B_X) : "memory");
                if (roleA)
                    asm volatile("cp.async.bulk.shared::cluster.global.mbarrier::complete_tx::bytes [%0], [%1], 1280, [%2];"
                                 :: "r"(sbase + OFF_XS + 1280), "l"(prm.gw), "r"(bars + 8 * B_X) : "memory");
            } else {
                asm volatile("mbarrier.init.shared::cta.b64 [%0], 1;" :: "r"(bars + 8 * k) : "memory");
                if (roleA || k != B_EX2) expect_tx(bars + 8 * k, roleA ? (k == B_EX1 ? 256 : 4096) : 1024);
            }
#pragma unroll
            for (int i = 1; i < 9; ++i) asm volatile("mbarrier.init.shared::cta.b64 [%0], 1;" :: "r"(tb + 8 * (k + 4 * i)) : "memory");
            asm volatile("fence.mbarrier_init.release.cluster;" ::: "memory");
        }
        __syncwarp();
        asm volatile("barrier.cluster.arrive.relaxed.aligned;" ::: "memory");
        asm volatile("setmaxnreg.dec.sync.aligned.u32 32;");
        const int total = roleA ? (ffn ? A_END : A_W1) : P_END;
        const uint32_t tp = t0 + ((me * prm.ph) >> 6);
#define MONITOR()
#pragma unroll 1
        for (int i = roleA ? k : k + 4; i < total; i += 4) {
            const uint4 e = prm.tile[roleA][i];
            const uint32_t c0 = (e.z & 0xffffu) + 32 * ((e.w & 255u) * id + ((e.w >> 8) & 255u) * r);
            const uint32_t c1 = (e.z >> 16) + 32 * (((e.w >> 16) & 255u) * id + (e.w >> 24) * r);
            if (i >= CAP) mbar_wait(tb + 8 * (i - CAP));
            if (!roleA && i >= P_WO && i < P_WO + 4) {
                asm volatile("barrier.cluster.wait.aligned;" ::: "memory");
                mbar_wait(bars + 8 * B_EX0);
            }
            if (lane == 0) expect_tx(tb + 8 * i, 8192u >> (e.x >> 24));
            while ((int)(now_ns() - tp) < (int)e.y) { MONITOR(); }
            if (lane == 0) {
                tma2d(sbase + (e.x & 0xfffffu), mapbase + 128 * ((e.x >> 20) & 7u), c0, c1, tb + 8 * i);
            }
            __syncwarp();
        }
        return;
    }

    asm volatile("setmaxnreg.inc.sync.aligned.u32 112;");
    Scratch* const scr = prm.scr;
    uint32_t epoch;
    asm volatile("ld.relaxed.gpu.global.u32 %0, [%1];" : "=r"(epoch) : "l"(&scr->epoch) : "memory");
    asm volatile("barrier.cluster.arrive.relaxed.aligned;" ::: "memory");
    asm volatile("barrier.cluster.wait.aligned;" ::: "memory");
    if (!roleA) asm volatile("cp.async.mbarrier.arrive.noinc.shared::cta.b64 [%0];" :: "r"(tb + 8 * (warp >> 2)) : "memory");
    const uint32_t tag = (epoch & 1u) ^ 1u;
    const int g = lane >> 2, tq = lane & 3;
    const uint32_t tsw = sbase + ((lane & 7) + (lane >> 4) * 8) * 128 + (((2 * (warp & 3) + ((lane >> 3) & 1)) ^ (lane & 7)) << 4);
    float d[16];
    const bool reducer = roleA && me >= 24;
    const u64* rsrc = &scr->x4[me - 24][8 * warp][2 * lane];
    uint4 rv = make_uint4(tag, 0u, tag, 0u);
    if (reducer && t < 118 * 4) rv = ld_pkt2(rsrc);
    mbar_wait(bars + 8 * B_X);

    if (roleA) {
        uint32_t fa[64];
        const int wg = warp >> 2;
        const uint32_t sbar = bars + 8 * (wg ? B_EX2 : B_EX0);
        if (warp == 8) {
            float s = 0.f;
#pragma unroll 2
            for (int i = 0; i < 10; ++i) {
                const uint32_t xw = lds32(sbase + OFF_XS + (lane + 32 * i) * 4), gv = lds32(sbase + OFF_XS + 1280 + (lane + 32 * i) * 4);
                uint32_t pr;
                asm("mul.rn.bf16x2 %0, %1, %2;" : "=r"(pr) : "r"(xw), "r"(gv));
                s += bf_lo(pr) + bf_hi(pr);
            }
#pragma unroll
            for (int k = 16; k > 0; k >>= 1) s += shx(s, k);
            const float ga = bf_round(__fdividef(1.0f, 1.0f + __expf(-bf_round(s))));
            if (lane == 0) sts128(sbase + OFF_EX0, make_uint4(__float_as_uint(ga), __float_as_uint(bf_round(1.0f - ga)), 0xffff0000u, 0u));
        }
        if (warp == 15) sts32(sbase + OFF_SMAX + 4 * lane, 0x80000000u);
#define PRELOAD() do { mbar_wait2(tb + 8 * (A_C + (wg & 1) + 2 * (~wg & 2)), tb + 8 * (A_C + 2 + (wg & 1) + 2 * (~wg & 2))); \
        _Pragma("unroll") for (int ks = 0; ks < 8; ++ks) ldsm4t(fa + 4 * ks, tsw + OFF_C + wg * 16384 + ks * 2048); } while (0)
        const int h0 = 4 * (warp - 8);
        const int hq = h0 + (lane >> 3);
        const u64* src = &scr->x1[2 * hq + r][2 * (lane & 7)];
        const uint32_t qa = sbase + OFF_Q + hq * 128 + (((lane ^ hq) & 7) << 4);
        uint4 v[4];
        if (warp < 8) {
            const uint32_t base = sbase + OFF_C + (16 * warp + (lane & 7) + ((lane >> 3) & 1) * 8) * 128;
            const u64 qd = sdesc(sbase + OFF_Q);
            const uint32_t rdst = peer_addr(sbase + OFF_SREM + t * 16, r ^ 1), rbar = peer_addr(sbar, r ^ 1);
            pin(rdst); pin(rbar);
            zero16(d);
#pragma unroll
            for (int ci = 0; ci < 4; ++ci) {
                const int cb = ci ^ 2;
                mbar_wait(tb + 8 * (A_C + 2 * wg + (ci & 1) + 2 * (ci & 2)));
#pragma unroll
                for (int k = 0; k < 4; ++k) ldsm4(fa + 16 * cb + 4 * k, base + cb * 16384 + (((2 * k + (lane >> 4)) ^ (lane & 7)) << 4));
            }
            TLT(1, 128);
            bar_sync(BAR_Q + wg, 384);
            TLT(2, 0);
            asm volatile("wgmma.fence.sync.aligned;" ::: "memory");
#pragma unroll
            for (int ks = 0; ks < 16; ++ks) wgmma_rs(d, fa + 4 * ks, qd + (ks >> 2) * 256 + (ks & 3) * 2);
            asm volatile("wgmma.commit_group.sync.aligned;" ::: "memory");
            asm volatile("wgmma.wait_group.sync.aligned 0;" ::: "memory");
#pragma unroll
            for (int i = 0; i < 2; ++i)
                asm volatile("st.async.shared::cluster.mbarrier::complete_tx::bytes.v4.b32 [%0], {%1,%2,%3,%4}, [%5];"
                             :: "r"(rdst + i * 4096), "r"(pack_bf(d[8 * i], d[8 * i + 1])), "r"(pack_bf(d[8 * i + 2], d[8 * i + 3])),
                                "r"(pack_bf(d[8 * i + 4], d[8 * i + 5])), "r"(pack_bf(d[8 * i + 6], d[8 * i + 7])), "r"(rbar) : "memory");
            TLT(3, 0);
            TLT(17, 128);
        } else {
            pin(src); pin(qa);
            wait_until(t0, prm.tq0);
#pragma unroll
            for (int k = 0; k < 3; ++k) v[k] = ld_pkt2(src + 16 * k);
            while ((int)(now_ns() - t0) < prm.tq) { }
            TLT(8, 256);
            v[3] = ld_pkt2(src + 48);
        }
        PRELOAD();
        if (warp >= 8) {
#pragma unroll 1
            for (int it = 0; it < SPIN_MAX; ++it) {
                if (__all_sync(0xffffffffu, fresh2(v[0], tag) && fresh2(v[1], tag) && fresh2(v[2], tag) && fresh2(v[3], tag))) break;
#pragma unroll
                for (int k = 0; k < 4; ++k) if (!fresh2(v[k], tag)) v[k] = ld_pkt2(src + 16 * k);
                TLT(20, 256);
            }
#pragma unroll
            for (int k = 0; k < 4; ++k) {
                v[k].x &= ~1u; v[k].z &= ~1u;
                sts128(qa + k * 4096, v[k]);
            }
            asm volatile("fence.proxy.async.shared::cta;" ::: "memory");
            asm volatile("bar.arrive %0, 384;" :: "r"(BAR_Q) : "memory");
            asm volatile("bar.arrive %0, 384;" :: "r"(BAR_Q + 1) : "memory");
            TLT(9, 256);
            if (warp >= 14) {
                mbar_wait2(bars + 8 * B_EX0, bars + 8 * B_EX2);
                const uint32_t ts = tag_word(now_ns(), tag);
                st_pkt2(&scr->sig[2 * (16 * (warp & 1) + (lane >> 1)) + r][id][2 * (lane & 1)], make_uint4(ts, 0u, ts, 0u));
            }
        }
        const bool b4 = lane & 16, b3 = lane & 8, b2 = lane & 4;
        const int myhead = 8 * (g >> 1) + 2 * tq + (g & 1);
        const u64 pd = sdesc(sbase + OFF_P);
        const uint32_t oa = sbase + OFF_OT + ((lane & 7) + (lane >> 4) * 8) * 528 + warp * 32 + ((lane >> 3) & 1) * 16;
        const int hh = (t & 127) >> 3;
        const uint32_t ob = sbase + OFF_OT + hh * 528 + wg * 128 + (lane & 7) * 16;
        u64* const xdst = &scr->x2[2 * hh + r][id][16 * wg + 2 * (lane & 7)];
        pin(oa); pin(ob); pin(xdst);
        float u[8];
        if (warp < 8) {
            mbar_wait(sbar);
            TLT(4, 0);
            TLT(18, 128);
#pragma unroll
            for (int i = 0; i < 2; ++i) {
                const uint4 o = lds128(sbase + OFF_SREM + t * 16 + i * 4096);
                d[8 * i] += bf_lo(o.x); d[8 * i + 1] += bf_hi(o.x); d[8 * i + 2] += bf_lo(o.y); d[8 * i + 3] += bf_hi(o.y);
                d[8 * i + 4] += bf_lo(o.z); d[8 * i + 5] += bf_hi(o.z); d[8 * i + 6] += bf_lo(o.w); d[8 * i + 7] += bf_hi(o.w);
            }
#pragma unroll
            for (int i = 0; i < 8; ++i) u[i] = fmaxf(d[4 * (i >> 1) + (i & 1)], d[4 * (i >> 1) + (i & 1) + 2]);
#pragma unroll
            for (int i = 0; i < 4; ++i) u[i] = fmaxf(b4 ? u[i + 4] : u[i], shx(b4 ? u[i] : u[i + 4], 16));
#pragma unroll
            for (int i = 0; i < 2; ++i) u[i] = fmaxf(b3 ? u[i + 2] : u[i], shx(b3 ? u[i] : u[i + 2], 8));
            asm volatile("red.shared.max.s32 [%0], %1;" :: "r"(sbase + OFF_SMAX + 4 * myhead),
                         "r"(f2ord(__float_as_int(fmaxf(b2 ? u[1] : u[0], shx(b2 ? u[0] : u[1], 4))))) : "memory");
            bar_sync(BAR_HALF, 256);
            TLT(13, 0);
            uint32_t pk[8];
#pragma unroll
            for (int j = 0; j < 4; ++j) {
                const uint2 mi = lds64(sbase + OFF_SMAX + 32 * j + 8 * tq);
                const float m0 = __int_as_float(f2ord((int)mi.x)), m1 = __int_as_float(f2ord((int)mi.y));
                pk[2 * j] = pack_bf(ex2(d[4 * j] - m0), ex2(d[4 * j + 1] - m1));
                pk[2 * j + 1] = pack_bf(ex2(d[4 * j + 2] - m0), ex2(d[4 * j + 3] - m1));
            }
            stsm4t(tsw + OFF_P + wg * 4096, pk);
            stsm4t(tsw + OFF_P + wg * 4096 + 2048, pk + 4);
            asm volatile("fence.proxy.async.shared::cta;" ::: "memory");
            asm volatile("bar.arrive %0, 512;" :: "r"(BAR_ALL) : "memory");
            const uint32_t hm = lds32(sbase + OFF_EX0 + 8);
#pragma unroll
            for (int j = 0; j < 4; ++j) {
                u[2 * j] = F((pk[2 * j] << 16) & hm) + bf_lo(pk[2 * j + 1]);
                u[2 * j + 1] = F(pk[2 * j] & hm) + bf_hi(pk[2 * j + 1]);
            }
#pragma unroll
            for (int i = 0; i < 4; ++i) u[i] = (b4 ? u[i + 4] : u[i]) + shx(b4 ? u[i] : u[i + 4], 16);
#pragma unroll
            for (int i = 0; i < 2; ++i) u[i] = (b3 ? u[i + 2] : u[i]) + shx(b3 ? u[i] : u[i + 2], 8);
            sts32(sbase + OFF_LSUM + (warp * 32 + myhead) * 4, __float_as_uint((b2 ? u[1] : u[0]) + shx(b2 ? u[0] : u[1], 4)));
            zero16(d);
            bar_sync(BAR_HALF, 256);
        } else {
            zero16(d);
            bar_sync(BAR_ALL, NCOMP);
        }
        TLT(5, 256);
        asm volatile("wgmma.fence.sync.aligned;" ::: "memory");
#pragma unroll
        for (int ks = 0; ks < 8; ++ks) wgmma_rs(d, fa + 4 * ks, pd + (ks >> 2) * 256 + (ks & 3) * 2);
        asm volatile("wgmma.commit_group.sync.aligned;" ::: "memory");
        if (wg == 0) {
            const int h2 = 8 * warp + g;
            float l = ldsf(sbase + OFF_LSUM + (tq * 64 + h2) * 4) + ldsf(sbase + OFF_LSUM + (tq * 64 + 32 + h2) * 4);
            const uint32_t mw = lds32(sbase + OFF_SMAX + 4 * h2);
            l += shx(l, 1);
            l += shx(l, 2);
            const uint32_t lw = tag_word(__float_as_uint(l), tag);
            st_pkt2(&scr->st[2 * h2 + r][id][2 * tq], make_uint4(lw, mw, lw, mw));
        }
        asm volatile("wgmma.wait_group.sync.aligned 0;" ::: "memory");
        {
            uint32_t pk[8];
#pragma unroll
            for (int i = 0; i < 8; ++i) pk[i] = pack_bf(d[2 * i], d[2 * i + 1]);
            stsm4t(oa, pk);
            stsm4t(oa + 16 * 528, pk + 4);
            bar_sync(BAR_WG + wg, 128);
            TLT(14, 128);
#pragma unroll
            for (int i = 0; i < 2; ++i) {
                uint4 v = lds128(ob + i * 16 * 528);
                v.x = tag_word(v.x, tag); v.z = tag_word(v.z, tag);
                st_pkt2(xdst + i * (32 * 32 * 64), v);
            }
        }
        TLT(19, 256);
        TLT(6, 128);
    }

    if (roleA ? (ffn && warp < 4) : warp < 8) {
        const uint32_t step = roleA ? 1 : 2;
        uint32_t xa = sbase + OFF_XS + 640 * r + (lane >> 3) * 16;
        uint32_t wa = tsw + (roleA ? OFF_W1 : OFF_WO + (warp >> 2) * 8192);
        uint32_t bar = tb + 8 * (roleA ? A_W1 : P_WQ + (warp >> 2));
        const int col = 16 * warp + g + 8 * (tq & 1);
        const uint32_t rank = roleA ? warp >> 1 : tq >> 1;
        const uint32_t rdst = peer_addr(sbase + (roleA ? OFF_EX1 + (r * 32 + (col & 31)) * 4 : OFF_EX0 + (r * 128 + col) * 4), rank);
        const uint32_t rbar = peer_addr(bars + 8 * (roleA ? B_EX1 : B_EX0), rank);
        pin(rdst); pin(rbar);
        zero16(d);
#pragma unroll 1
        for (int kb = 0; kb < 5; ++kb) {
            uint32_t b[8], a[16];
            ldsm4(b, xa); ldsm4(b + 4, xa + 64);
            mbar_wait(bar);
#pragma unroll
            for (int k = 0; k < 4; ++k) ldsm4t(a + 4 * k, wa + k * 2048);
#pragma unroll
            for (int k = 0; k < 4; ++k) mma_w(d + 4 * k, a + 4 * k, b[2 * k], b[2 * k + 1]);
            xa += 128; wa += step * 8192; bar += step * 8;
        }
        const float v = (tq & 1) ? (d[2] + d[6]) + (d[10] + d[14]) : (d[0] + d[4]) + (d[8] + d[12]);
        if (!roleA || tq < 2) st_async1(rdst, v, rbar);
    }

    if (!roleA) {
        TLT(1, 0);
        {
            const uint32_t base = sbase + OFF_WUK + (warp >> 2) * 16384 + ((warp & 3) * 16 + (lane & 7) + ((lane >> 3) & 1) * 8) * 128;
            u64* const qdst = &scr->x1[me][4 * warp + 2 * tq + (lane >> 4)];
            pin(base); pin(qdst);
            mbar_wait(bars + 8 * B_EX0);
            const uint4 q0 = lds128(sbase + OFF_EX0 + lane * 16), q1 = lds128(sbase + OFF_EX0 + 512 + lane * 16);
            const uint32_t w0 = pack_bf(F(q0.x) + F(q1.x), F(q0.y) + F(q1.y)), w1 = pack_bf(F(q0.z) + F(q1.z), F(q0.w) + F(q1.w));
            sts64(sbase + OFF_O + lane * 8, w0, w1);
            __syncwarp();
            uint32_t b[16];
#pragma unroll
            for (int k = 0; k < 4; ++k) ldsm4(b + 4 * k, sbase + OFF_O + (lane >> 3) * 16 + 64 * k);
            TLT(2, 0);
            zero16(d);
            mbar_wait2(tb + 8 * (P_WUK + 2 * (warp >> 2)), tb + 8 * (P_WUK + 2 * (warp >> 2) + 1));
            uint32_t a[32];
#pragma unroll
            for (int k = 0; k < 8; ++k) ldsm4(a + 4 * k, base + (k >> 2) * 8192 + (((2 * (k & 3) + (lane >> 4)) ^ (lane & 7)) << 4));
#pragma unroll
            for (int k = 0; k < 8; ++k) mma_w(d + 4 * (k & 3), a + 4 * k, b[2 * k], b[2 * k + 1]);
            const float sc = 0.08838834764831845f * 1.4426950408889634f;
            const float v = ((tq & 1) ? (d[2] + d[6]) + (d[10] + d[14]) : (d[0] + d[4]) + (d[8] + d[12])) * sc;
            const uint32_t w = pack_bf(v, __shfl_down_sync(0xffffffffu, v, 4));
            const uint32_t w2 = __shfl_down_sync(0xffffffffu, w, 8);
            if ((lane & 14) == 0) st_pkt(qdst, tag_word(w, tag), w2);
        }
        TLT(3, 480);
        {
            uint32_t a[32];
            const int a0 = 4 * (warp >> 1);
            const u64* src = &scr->x2[me][a0][32 * (warp & 1) + lane];
            const u64* ssrc = &scr->st[me][a0 + (lane & 3)][0];
            const uint32_t rank = (warp >> 2) & 1;
            const uint32_t rdst = peer_addr(sbase + OFF_EX1 + ((2 * r + (warp >> 3)) * 64 + 16 * (warp & 3) + g + 8 * (tq & 1)) * 4, rank);
            const uint32_t rbar = peer_addr(bars + 8 * B_EX1, rank);
            const uint32_t ow = sbase + OFF_O + (warp >> 1) * 528 + (warp & 1) * 256 + lane * 8;
            const uint32_t ol = sbase + OFF_O + (lane & 7) * 528 + (warp >> 3) * 256 + (lane >> 3) * 16;
            pin(src); pin(ssrc); pin(rdst); pin(rbar); pin(ow); pin(ol);
            if (warp == 15) {
                wait_until(t0, prm.ts);
                uint2 s = ld_pkt(&scr->sig[me][lane][0]);
#pragma unroll 1
                for (int it = 0; it < SPIN_MAX; ++it) {
                    const bool ok = ((s.x ^ tag) & 1u) == 0;
                    if (__all_sync(0xffffffffu, ok)) break;
                    __nanosleep(100);
                    if (!ok) s = ld_pkt(&scr->sig[me][lane][0]);
                }
                const int last = __reduce_max_sync(0xffffffffu, (int)(s.x - t0));
                if (lane == 0) {
                    sts32(sbase + OFF_LSUM, t0 + last + prm.lb);
                    asm volatile("mbarrier.arrive.shared::cta.b64 _, [%0];" :: "r"(bars + 8 * B_EX2) : "memory");
                }
            }
            const int ti = 4 * (warp >> 3) + ((warp >> 2) & 1);
            mbar_wait2(tb + 8 * (P_WUV + ti), tb + 8 * (P_WUV + ti + 2));
#pragma unroll
            for (int k = 0; k < 8; ++k) ldsm4t(a + 4 * k, tsw + OFF_WUV + ti * 8192 + (k >> 2) * 16384 + (k & 3) * 2048);
            zero16(d);
            mbar_wait(bars + 8 * B_EX2);
            TLT(4, 0);
            const uint32_t tgo = lds32(sbase + OFF_LSUM) - (warp & 1) * prm.lb1;
            while ((int)(now_ns() - tgo) < 0) { }
            TLT(14, 0);
            uint2 v[5];
            v[4] = ld_pkt(ssrc);
#pragma unroll
            for (int i = 0; i < 4; ++i) v[i] = ld_pkt(src + 64 * i);
#pragma unroll 1
            for (int it = 0; it < SPIN_MAX; ++it) {
                if (__all_sync(0xffffffffu, (((v[0].x ^ tag) | (v[1].x ^ tag) | (v[2].x ^ tag) | (v[3].x ^ tag) | (v[4].x ^ tag)) & 1u) == 0)) break;
#pragma unroll
                for (int i = 0; i < 5; ++i) if ((v[i].x ^ tag) & 1u) v[i] = ld_pkt(i < 4 ? src + 64 * i : ssrc);
                TLT(20, 0);
            }
            TLT(5, 0);
            const int mgrp = __reduce_max_sync(0xffffffffu, (int)v[4].y);
            const float e = ex2(__int_as_float(f2ord((int)v[4].y)) - __int_as_float(f2ord(mgrp)));
            float c[4] = {0.f, 0.f, 0.f, 0.f};
#pragma unroll
            for (int i = 0; i < 4; ++i) {
                const float wn = __shfl_sync(0xffffffffu, e, i);
                c[0] = fmaf(wn, bf_lo(v[i].x & ~1u), c[0]); c[1] = fmaf(wn, bf_hi(v[i].x), c[1]);
                c[2] = fmaf(wn, bf_lo(v[i].y), c[2]); c[3] = fmaf(wn, bf_hi(v[i].y), c[3]);
            }
            sts64(ow, pack_bf(c[0], c[1]), pack_bf(c[2], c[3]));
            if (lane < 4) sts64(sbase + OFF_SMAX + (a0 + lane) * 8, (uint32_t)mgrp, __float_as_uint(e * F(v[4].x & ~1u)));
            bar_sync(BAR_ALL, NCOMP);
            TLT(6, 0);
            uint32_t b[16];
#pragma unroll
            for (int k = 0; k < 4; ++k) ldsm4(b + 4 * k, ol + 64 * k);
            const uint2 gs = lds64(sbase + OFF_SMAX + lane * 8);
#pragma unroll
            for (int k = 0; k < 8; ++k) mma_w(d + 4 * (k & 3), a + 4 * k, b[2 * k], b[2 * k + 1]);
            const float eg = ex2(__int_as_float(f2ord((int)gs.x)) - __int_as_float(f2ord(__reduce_max_sync(0xffffffffu, (int)gs.x))));
            const float e0 = __shfl_sync(0xffffffffu, eg, 8 * tq), e1 = __shfl_sync(0xffffffffu, eg, 8 * tq + 4);
            const float c0 = e0 * ((d[0] + d[4]) + (d[8] + d[12])) + e1 * ((d[1] + d[5]) + (d[9] + d[13]));
            const float c1 = e0 * ((d[2] + d[6]) + (d[10] + d[14])) + e1 * ((d[3] + d[7]) + (d[11] + d[15]));
            float v_ = ((tq & 1) ? c1 : c0) + shx((tq & 1) ? c0 : c1, 1);
            float lg = eg * F(gs.y);
#pragma unroll
            for (int s = 16; s > 0; s >>= 1) lg += shx(lg, s);
            v_ += shx(v_, 2);
            if (tq < 2) st_async1(rdst, __fdividef(v_, lg), rbar);
            TLT(15, 0);
        }
    }

    if (!roleA || ffn) {
        const uint32_t tsz = roleA ? 4096 : 8192;
        const uint32_t wa = tsw + (roleA ? OFF_W2 : OFF_WO) + (warp >> 2) * tsz;
        const uint32_t bar = tb + 8 * ((roleA ? A_W2 : P_WO) + (warp >> 2));
        u64* const dst = &scr->x4[warp][roleA ? 64 + me : me][g];
        uint32_t a[32];
#pragma unroll
        for (int i = 0; i < 1 + FIN2; ++i) {
            mbar_wait(bar + 32 * i);
            ldsm4t(a + 16 * i, wa + 4 * i * tsz); ldsm4t(a + 16 * i + 4, wa + 4 * i * tsz + 2048);
            if (!roleA) { ldsm4t(a + 16 * i + 8, wa + 4 * i * tsz + 4096); ldsm4t(a + 16 * i + 12, wa + 4 * i * tsz + 6144); }
        }
        pin(dst);
        mbar_wait(bars + 8 * B_EX1);
        TLT(7, 0);
        uint32_t w;
        if (!roleA) {
            const uint32_t ep = sbase + OFF_EX1 + lane * 8;
            const uint2 e0 = lds64(ep), e1 = lds64(ep + 256), e2 = lds64(ep + 512), e3 = lds64(ep + 768);
            w = pack_bf((F(e0.x) + F(e1.x)) + (F(e2.x) + F(e3.x)), (F(e0.y) + F(e1.y)) + (F(e2.y) + F(e3.y)));
        } else {
            const uint32_t ep = sbase + OFF_EX1 + (lane & 15) * 8;
            const uint2 e0 = lds64(ep), e1 = lds64(ep + 128);
            const float h0 = bf_round(F(e0.x) + F(e1.x)), h1 = bf_round(F(e0.y) + F(e1.y));
            w = pack_bf(__fdividef(h0, 1.0f + __expf(-h0)), __fdividef(h1, 1.0f + __expf(-h1)));
        }
        uint32_t bv[8];
#pragma unroll
        for (int i = 0; i < 8; ++i) bv[i] = __shfl_sync(0xffffffffu, w, 4 * i + tq);
#pragma unroll 1
        for (int i = 0;; ++i) {
            zero16(d);
            mma_w(d, a, bv[0], bv[1]); mma_w(d + 4, a + 4, bv[2], bv[3]);
            if (!roleA) { mma_w(d + 8, a + 8, bv[4], bv[5]); mma_w(d + 12, a + 12, bv[6], bv[7]); }
            const bool more = warp + 16 * i < 24;
            uint32_t rdy = 1;
            if (more) asm volatile("{.reg .pred p; mbarrier.test_wait.parity.shared::cta.b64 p, [%1], 0; selp.u32 %0,1,0,p;}" : "=r"(rdy) : "r"(bar + 32 * i + 32) : "memory");
            if (tq == 0) st_pkt(dst + i * (16 * 128 * 8), tag_word(__float_as_uint((d[0] + d[4]) + (d[8] + d[12])), tag), __float_as_uint((d[2] + d[6]) + (d[10] + d[14])));
            if (!more) break;
            if (!rdy) mbar_wait(bar + 32 * i + 32);
            const uint32_t wn = wa + 4 * (i + 1) * tsz;
            ldsm4t(a, wn); ldsm4t(a + 4, wn + 2048);
            if (!roleA) { ldsm4t(a + 8, wn + 4096); ldsm4t(a + 12, wn + 6144); }
        }
    }
    TLT(10, 0);
    if (reducer) {
        const uint32_t rw = sbase + OFF_O + (warp * 16 + 2 * tq + (lane >> 4) + (lane & 8)) * 4;
        const uint32_t rp = sbase + OFF_O + ((lane >> 4) * 128 + (lane & 15)) * 4;
        __nv_bfloat16* const op = prm.out + 16 * (me - 24) + (lane & 15);
        const float gg = ldsf(sbase + OFF_EX0 + (warp >> 3) * 4);
        pin(rw); pin(rp); pin(op);
#pragma unroll 1
        for (int it = 0; it < SPIN_MAX; ++it) {
            const bool ok = fresh2(rv, tag);
            if (__all_sync(0xffffffffu, ok)) break;
            if (!ok) rv = ld_pkt2(rsrc);
        }
        const bool b4 = lane & 16, b3 = lane & 8;
        const float o0 = F(rv.x & ~1u), o1 = F(rv.y), o2 = F(rv.z & ~1u), o3 = F(rv.w);
        const float y0 = (b4 ? o2 : o0) + shx(b4 ? o0 : o2, 16), y1 = (b4 ? o3 : o1) + shx(b4 ? o1 : o3, 16);
        float y = (b3 ? y1 : y0) + shx(b3 ? y0 : y1, 8);
        y += shx(y, 4);
        if (!(lane & 4)) sts32(rw, __float_as_uint(gg * y));
        if (warp != 15) asm volatile("bar.arrive %0, 512;" :: "r"(BAR_Q) : "memory");
        else {
            bar_sync(BAR_Q, NCOMP);
            float z = ((ldsf(rp) + ldsf(rp + 64)) + (ldsf(rp + 128) + ldsf(rp + 192))) + ((ldsf(rp + 256) + ldsf(rp + 320)) + (ldsf(rp + 384) + ldsf(rp + 448)));
            z += shx(z, 16);
            if (lane < 16) *op = __float2bfloat16_rn(z);
            if (me == 24 && lane == 0) asm volatile("st.relaxed.gpu.global.u32 [%0], %1;" :: "l"(&scr->epoch), "r"(epoch + 1u) : "memory");
            TLT(11, 480);
        }
    }
}

typedef CUresult (*EncodeFn)(CUtensorMap*, CUtensorMapDataType, cuuint32_t, void*, const cuuint64_t*, const cuuint64_t*,
                             const cuuint32_t*, const cuuint32_t*, CUtensorMapInterleave, CUtensorMapSwizzle,
                             CUtensorMapL2promotion, CUtensorMapFloatOOBfill);

void make_map(EncodeFn enc, CUtensorMap* m, void* base, uint64_t cols, uint64_t rows, uint32_t brows = 64) {
    cuuint64_t dims[2] = {cols, rows};
    cuuint64_t strides[1] = {cols * 2};
    cuuint32_t box[2] = {64, brows};
    cuuint32_t es[2] = {1, 1};
    enc(m, CU_TENSOR_MAP_DATA_TYPE_BFLOAT16, 2, base, dims, strides, box, es, CU_TENSOR_MAP_INTERLEAVE_NONE,
        CU_TENSOR_MAP_SWIZZLE_128B, CU_TENSOR_MAP_L2_PROMOTION_NONE, CU_TENSOR_MAP_FLOAT_OOB_FILL_NONE);
}

}

extern "C" void kernel_launch(void* const* d_in, const int* in_sizes, int n_in, void* d_out, int out_size) {
    (void)in_sizes; (void)n_in; (void)out_size;
    static EncodeFn enc = nullptr;
    static void* scr = nullptr;
    if (!enc) {
        cudaFuncSetAttribute(fused_kernel, cudaFuncAttributeMaxDynamicSharedMemorySize, SMEM_BYTES);
        cudaGetSymbolAddress(&scr, g_scr);
        void* fn = nullptr;
        cudaDriverEntryPointQueryResult qr;
        cudaGetDriverEntryPoint("cuTensorMapEncodeTiled", &fn, cudaEnableDefault, &qr);
        enc = (EncodeFn)fn;
    }
    Params prm;
    prm.x = (const __nv_bfloat16*)d_in[0];
    prm.gw = (const __nv_bfloat16*)d_in[9];
    prm.out = (__nv_bfloat16*)d_out;
    prm.scr = (Scratch*)scr;
    const Tune tn = tune();
    prm.tq0 = tn.TQ0; prm.tq = tn.TQ; prm.ts = tn.TS; prm.lb = tn.LB; prm.lb1 = tn.LB1; prm.ph = tn.PH;
    for (int i = 0; i < 36; ++i) {
        auto mk = [&](int dst, int map, int half, int when, int c0, int c1, int c0i, int c0r, int c1i, int c1r) {
            if (map == 2 || map == 3 || map >= 5) {
                const int v = when - tn.T3, a = v < tn.V1 ? v : tn.V1, c = v > tn.V2 ? v - tn.V2 : 0, b = v - a - c;
                when = tn.T3 + (a * tn.S1 + b * tn.S2 + c * tn.S3) / 100;
            }
            return make_uint4(dst | map << 20 | half << 24, when + tn.OFF, c0 | c1 << 16, c0i / 32 | c0r / 32 << 8 | c1i / 32 << 16 | c1r / 32 << 24);
        };
        const int j = i - P_WUV;
        const int wp = j < 0 ? (i - 3) * tn.DD1 : tn.T3 + (j < tn.NP2 ? j : tn.NP2) * tn.DP2 + (j > tn.NP2 ? j - tn.NP2 : 0) * tn.DP3;
        prm.tile[0][i] = i < P_WUK ? mk(OFF_WO + i * 8192, 0, 0, wp, 64 * (i & 1), 64 * (i >> 1), 128, 0, 0, 320)
                       : i < P_WO  ? mk((i - P_WUK) * 8192, i < P_WUV ? 1 : 2, 0, wp, 64 * (i & 1), 64 * (((i - P_WUK) >> 1) & 3), 128, 0, 0, 256)
                                   : mk(OFF_WO + (i - P_WO) * 8192, 3, 0, wp, 64 * (i - P_WO), 0, 0, 0, 128, 64);
        const int cb = (i & 1) + (i < 4 ? 2 : 0), kh = (i >> 1) & 1;
        prm.tile[1][i] = i < A_W1 ? mk(cb * 16384 + kh * 8192, 4, 0, tn.TA1 + i * tn.DA1, 64 * cb, 64 * kh, 0, 256, 128, 0)
                       : i < A_W2 ? mk(i * 8192, 5, 0, tn.T3 + (i - A_W1) * tn.DA2, 0, 64 * (i - A_W1), 64, 0, 0, 320)
                                  : mk(OFF_W2 + (i - A_W2) * 4096, 6, 1, tn.T3 + 5 * tn.DA2 + (i - A_W2) * (tn.DA2 / 2), 64 * (i - A_W2), 0, 0, 0, 64, 32);
    }
    make_map(enc, &prm.m[0], d_in[2], 4096, MD);
    make_map(enc, &prm.m[1], d_in[3], 4096, DC);
    make_map(enc, &prm.m[2], d_in[4], 4096, DC);
    make_map(enc, &prm.m[3], d_in[5], MD, 4096);
    make_map(enc, &prm.m[4], d_in[1], DC, SK);
    make_map(enc, &prm.m[5], d_in[7], FF, MD);
    make_map(enc, &prm.m[6], d_in[8], MD, FF, 32);
    fused_kernel<<<NCTA, NTHREADS, SMEM_BYTES>>>((const __nv_bfloat16*)d_in[2], prm);
}
```

```cpp
#include <cuda_runtime.h>
#include <cuda_bf16.h>
#include <cuda.h>
#include <stdint.h>
#include <stdlib.h>

namespace {

typedef unsigned long long u64;
constexpr int MD = 640, DC = 512, SK = 4096, FF = 1728;
constexpr int NCTA = 128;
constexpr int NCOMP = 512;
constexpr int NTHREADS = NCOMP + 128;
constexpr int SPIN_MAX = 1 << 20;

struct Tune { int DD, TP1, DD1, TA1, DA1, T3, DP2, DA2, DP3, TQ0, TQ, TS, LB, LS, PH, V1, V2, S1, S2, S3; };
#define TV(n, d) (d)
static Tune tune() {
    Tune t;
    t.DD = TV(DD, 168);
    t.DD1 = TV(DD1, 170);
    t.TP1 = TV(TP1, 2360);
    t.TA1 = TV(TA1, 2550);
    t.DA1 = TV(DA1, 152);
    t.T3 = TV(T3, 4180);
    t.DP2 = TV(DP2, 236);
    t.DA2 = TV(DA2, 420);
    t.DP3 = TV(DP3, 238);
    t.TQ = TV(TQ, 4480);
    t.TS = TV(TS, 6700);
    t.LB = TV(LB, 1480);
    t.LS = TV(LS, 1250);
    t.TQ0 = TV(TQ0, 4300);
    t.PH = TV(PH, 200);
    t.V1 = TV(V1, 2000); t.V2 = TV(V2, 3200); t.S1 = TV(S1, 100); t.S2 = TV(S2, 100); t.S3 = TV(S3, 100);
    return t;
}
#define CAP 15
#define PREW 7
#define TWO 1
#define PRE 1
#define ROLEMIX 2

constexpr int OFF_WUK = 0, OFF_WUV = 65536, OFF_WO = 131072;
constexpr int OFF_C = 0, OFF_W1 = 65536, OFF_W2 = OFF_W1 + 40960;
constexpr int OFF_Q = OFF_W2 + 40960, OFF_P = OFF_Q + 16384, OFF_SREM = OFF_P + 8192, OFF_OT = OFF_SREM + 8192;
constexpr int OFF_XS = 212992;
constexpr int OFF_EX0 = OFF_XS + 2560;
constexpr int OFF_EX1 = OFF_EX0 + 1024;
constexpr int OFF_O = OFF_EX1 + 1024;
constexpr int OFF_SMAX = OFF_O + 4224;
constexpr int OFF_LSUM = OFF_SMAX + 256;
constexpr int OFF_TL = OFF_LSUM + 1024;
constexpr int OFF_BAR = OFF_TL + 256;
enum { B_X = 0, B_EX0 = 1, B_EX1 = 2, B_EX2 = 3, B_W = 4, B_T = 5, B_COUNT = B_T + 36 };
constexpr int SMEM_BYTES = OFF_BAR + B_COUNT * 8 + 1024;
static_assert(SMEM_BYTES <= 232448, "smem");
enum { P_WQ = 0, P_WUK = 10, P_WUV = 18, P_WO = 26, P_END = 36, A_C = 0, A_W1 = 8, A_W2 = 13, A_END = 18 };

struct Scratch {
    u64 x1[64][64];
    uint32_t x4[40][128][16];
    u64 x2[64][32][64];
    u64 sig[2][64][32][4];
    unsigned int epoch;
};
__device__ Scratch g_scr;

struct Params {
    const __nv_bfloat16* x;
    const __nv_bfloat16* gw;
    __nv_bfloat16* out;
    Scratch* scr;
    int tq0, tq, ts, lb, ls, ph;
    uint4 tile[2][36];
    CUtensorMap m[7];
};

#define TLT(i, th)

__device__ __forceinline__ uint32_t s_u32(const void* p) { return (uint32_t)__cvta_generic_to_shared(p); }
__device__ __forceinline__ float bf_lo(uint32_t w) { return __uint_as_float(w << 16); }
__device__ __forceinline__ float bf_hi(uint32_t w) { return __uint_as_float(w & 0xffff0000u); }
__device__ __forceinline__ float bf_round(float v) { return __bfloat162float(__float2bfloat16_rn(v)); }
__device__ __forceinline__ uint32_t pack_bf(float lo, float hi) {
    uint32_t r; asm("cvt.rn.bf16x2.f32 %0, %1, %2;" : "=r"(r) : "f"(hi), "f"(lo)); return r;
}
__device__ __forceinline__ float ex2(float v) { float r; asm("ex2.approx.ftz.f32 %0, %1;" : "=f"(r) : "f"(v)); return r; }
__device__ __forceinline__ uint32_t tag_word(uint32_t w, uint32_t tag) { return (w & ~1u) | tag; }
__device__ __forceinline__ void pin(uint32_t v) { asm volatile("{.reg .pred p; setp.eq.u32 p, %0, 0xfffffff1; @p st.shared.u32 [%0], %0;}" :: "r"(v) : "memory"); }
__device__ __forceinline__ void pin(const void* v) { asm volatile("{.reg .pred p; setp.eq.u64 p, %0, 1; @p st.global.u32 [%0], 0;}" :: "l"(v) : "memory"); }
__device__ __forceinline__ uint32_t lds32(uint32_t a) { uint32_t v; asm volatile("ld.shared.u32 %0, [%1];" : "=r"(v) : "r"(a) : "memory"); return v; }
__device__ __forceinline__ float ldsf(uint32_t a) { return __uint_as_float(lds32(a)); }
__device__ __forceinline__ uint2 lds64(uint32_t a) { uint2 v; asm volatile("ld.shared.v2.u32 {%0,%1}, [%2];" : "=r"(v.x), "=r"(v.y) : "r"(a) : "memory"); return v; }
__device__ __forceinline__ uint4 lds128(uint32_t a) {
    uint4 v; asm volatile("ld.shared.v4.u32 {%0,%1,%2,%3}, [%4];" : "=r"(v.x), "=r"(v.y), "=r"(v.z), "=r"(v.w) : "r"(a) : "memory"); return v;
}
__device__ __forceinline__ void sts32(uint32_t a, uint32_t v) { asm volatile("st.shared.u32 [%0], %1;" :: "r"(a), "r"(v) : "memory"); }
__device__ __forceinline__ void sts64(uint32_t a, uint32_t x, uint32_t y) { asm volatile("st.shared.v2.u32 [%0], {%1,%2};" :: "r"(a), "r"(x), "r"(y) : "memory"); }
__device__ __forceinline__ void sts128(uint32_t a, const uint4& v) {
    asm volatile("st.shared.v4.u32 [%0], {%1,%2,%3,%4};" :: "r"(a), "r"(v.x), "r"(v.y), "r"(v.z), "r"(v.w) : "memory");
}
#define F(x) __uint_as_float(x)

__device__ __forceinline__ void st_pkt(u64* p, uint32_t lo, uint32_t hi) {
    asm volatile("{.reg .b64 v; mov.b64 v, {%1,%2}; st.relaxed.gpu.global.b64 [%0], v;}" :: "l"(p), "r"(lo), "r"(hi) : "memory");
}
__device__ __forceinline__ void st_word(uint32_t* p, uint32_t v) { asm volatile("st.relaxed.gpu.global.u32 [%0], %1;" :: "l"(p), "r"(v) : "memory"); }
__device__ __forceinline__ uint4 ld_word4(const uint32_t* p) {
    uint4 v; asm volatile("ld.relaxed.gpu.global.v4.u32 {%0,%1,%2,%3}, [%4];" : "=r"(v.x), "=r"(v.y), "=r"(v.z), "=r"(v.w) : "l"(p) : "memory"); return v;
}
__device__ __forceinline__ uint2 ld_pkt(const u64* p) {
    uint2 v; asm volatile("{.reg .b64 v; ld.relaxed.gpu.global.b64 v, [%2]; mov.b64 {%0,%1}, v;}" : "=r"(v.x), "=r"(v.y) : "l"(p) : "memory"); return v;
}
__device__ __forceinline__ uint4 ld_pkt2(const u64* p) {
    uint4 v; asm volatile("{.reg .b64 a,b; ld.relaxed.gpu.global.v2.b64 {a,b}, [%4]; mov.b64 {%0,%1}, a; mov.b64 {%2,%3}, b;}"
                          : "=r"(v.x), "=r"(v.y), "=r"(v.z), "=r"(v.w) : "l"(p) : "memory"); return v;
}
__device__ __forceinline__ bool fresh2(const uint4& v, uint32_t tag) { return (((v.x ^ tag) | (v.z ^ tag)) & 1u) == 0; }
__device__ __forceinline__ uint32_t now_ns() { uint32_t v; asm volatile("mov.u32 %0, %%globaltimer_lo;" : "=r"(v) :: "memory"); return v; }
__device__ __forceinline__ void wait_until(uint32_t t0, int when) {
    while ((int)(now_ns() - t0) < when - 400) __nanosleep(100);
    while ((int)(now_ns() - t0) < when) { }
}

__device__ __forceinline__ uint2 poll_pkt(const u64* p, uint32_t tag) {
    uint2 s = ld_pkt(p);
#pragma unroll 1
    for (int it = 0; it < SPIN_MAX; ++it) {
        const bool ok = ((s.x ^ tag) & 1u) == 0;
        if (__all_sync(0xffffffffu, ok)) break;
        __nanosleep(60);
        if (!ok) s = ld_pkt(p);
    }
    return s;
}

__device__ __forceinline__ void mbar_wait(uint32_t bar) {
    asm volatile("{\n.reg .pred p;\nLW:\nmbarrier.try_wait.parity.shared::cta.b64 p, [%0], 0;\n@!p bra.uni LW;\n}" :: "r"(bar) : "memory");
}
__device__ __forceinline__ void mbar_wait2(uint32_t bar0, uint32_t bar1) {
    asm volatile("{\n.reg .pred p, q;\nLW:\nmbarrier.try_wait.parity.shared::cta.b64 p, [%0], 0;\n"
                 "mbarrier.try_wait.parity.shared::cta.b64 q, [%1], 0;\nand.pred p, p, q;\n@!p bra.uni LW;\n}" :: "r"(bar0), "r"(bar1) : "memory");
}
__device__ __forceinline__ void expect_tx(uint32_t bar, uint32_t bytes) {
    asm volatile("mbarrier.arrive.expect_tx.relaxed.cta.shared::cta.b64 _, [%0], %1;" :: "r"(bar), "r"(bytes) : "memory");
}
__device__ __forceinline__ void tma3d(uint32_t dst, u64 map, uint32_t row, uint32_t blk, uint32_t bar) {
    asm volatile("cp.async.bulk.tensor.3d.shared::cluster.global.mbarrier::complete_tx::bytes [%0], [%1, {%5, %2, %3}], [%4];"
                 :: "r"(dst), "l"(map), "r"(row), "r"(blk), "r"(bar), "r"(0) : "memory");
}
__device__ __forceinline__ void bar_sync(int id, int n) { asm volatile("bar.sync %0, %1;" :: "r"(id), "r"(n) : "memory"); }
__device__ __forceinline__ uint32_t peer_addr(uint32_t a, uint32_t rank) {
    uint32_t r; asm("mapa.shared::cluster.u32 %0, %1, %2;" : "=r"(r) : "r"(a), "r"(rank)); return r;
}
__device__ __forceinline__ void st_async1(uint32_t dst, float a, uint32_t bar) {
    asm volatile("st.async.shared::cluster.mbarrier::complete_tx::bytes.f32 [%0], %1, [%2];" :: "r"(dst), "f"(a), "r"(bar) : "memory");
}
__device__ __forceinline__ void ldsm4(uint32_t* r, uint32_t a) {
    asm volatile("ldmatrix.sync.aligned.m8n8.x4.shared.b16 {%0,%1,%2,%3}, [%4];"
                 : "=r"(r[0]), "=r"(r[1]), "=r"(r[2]), "=r"(r[3]) : "r"(a) : "memory");
}
__device__ __forceinline__ void ldsm4t(uint32_t* r, uint32_t a) {
    asm volatile("ldmatrix.sync.aligned.m8n8.x4.trans.shared.b16 {%0,%1,%2,%3}, [%4];"
                 : "=r"(r[0]), "=r"(r[1]), "=r"(r[2]), "=r"(r[3]) : "r"(a) : "memory");
}
__device__ __forceinline__ void mma_w(float* c, const uint32_t* a, uint32_t b0, uint32_t b1) {
    asm volatile("mma.sync.aligned.m16n8k16.row.col.f32.bf16.bf16.f32 {%0,%1,%2,%3}, {%4,%5,%6,%7}, {%8,%9}, {%0,%1,%2,%3};"
                 : "+f"(c[0]), "+f"(c[1]), "+f"(c[2]), "+f"(c[3]) : "r"(a[0]), "r"(a[1]), "r"(a[2]), "r"(a[3]), "r"(b0), "r"(b1));
}
#define WG_D "{%0,%1,%2,%3,%4,%5,%6,%7,%8,%9,%10,%11,%12,%13,%14,%15}"
#define WG_DREGS "+f"(d[0]), "+f"(d[1]), "+f"(d[2]), "+f"(d[3]), "+f"(d[4]), "+f"(d[5]), "+f"(d[6]), "+f"(d[7]), \
                 "+f"(d[8]), "+f"(d[9]), "+f"(d[10]), "+f"(d[11]), "+f"(d[12]), "+f"(d[13]), "+f"(d[14]), "+f"(d[15])
__device__ __forceinline__ void wgmma_rs(float* d, const uint32_t* a, u64 desc) {
    asm volatile("wgmma.mma_async.sync.aligned.m64n32k16.f32.bf16.bf16 " WG_D ", {%16,%17,%18,%19}, %20, 1, 1, 1, 0;"
                 : WG_DREGS : "r"(a[0]), "r"(a[1]), "r"(a[2]), "r"(a[3]), "l"(desc) : "memory");
}
__device__ __forceinline__ void wgmma_ss(float* d, u64 adesc, u64 desc) {
    asm volatile("wgmma.mma_async.sync.aligned.m64n32k16.f32.bf16.bf16 " WG_D ", %16, %17, 1, 1, 1, 0, 0;"
                 : WG_DREGS : "l"(adesc), "l"(desc) : "memory");
}
__device__ __forceinline__ void zero16(float* d) {
#pragma unroll
    for (int i = 0; i < 16; ++i) { d[i] = 0.f; asm volatile("" : "+f"(d[i])); }
}
__device__ __forceinline__ void stsm4t(uint32_t a, const uint32_t* r) {
    asm volatile("stmatrix.sync.aligned.m8n8.x4.trans.shared.b16 [%0], {%1,%2,%3,%4};" :: "r"(a), "r"(r[0]), "r"(r[1]), "r"(r[2]), "r"(r[3]) : "memory");
}
__device__ __forceinline__ void st_pkt2(u64* p, const uint4& v) {
    asm volatile("{.reg .b64 a,b; mov.b64 a, {%1,%2}; mov.b64 b, {%3,%4}; st.relaxed.gpu.global.v2.b64 [%0], {a,b};}"
                 :: "l"(p), "r"(v.x), "r"(v.y), "r"(v.z), "r"(v.w) : "memory");
}
__device__ __forceinline__ u64 sdesc(uint32_t addr) {
    return (u64)((addr & 0x3FFFFu) >> 4) | (1ull << 16) | (64ull << 32) | (1ull << 62);
}
__device__ __forceinline__ float shx(float v, int m) { return __shfl_xor_sync(0xffffffffu, v, m); }

constexpr int BAR_ALL = 1, BAR_HALF = 2, BAR_L = 4, BAR_WG = 5, BAR_Q = 9;
__device__ __forceinline__ void spin(uint32_t n) { const uint32_t c = clock(); while ((uint32_t)clock() - c < n) { } }
__device__ __forceinline__ int f2ord(int b) { return b ^ ((b >> 31) & 0x7fffffff); }

__global__ void __cluster_dims__(2, 1, 1) __launch_bounds__(NTHREADS, 1)
fused_kernel(const __nv_bfloat16* __restrict__ wq, const __grid_constant__ Params prm) {
    extern __shared__ __align__(1024) unsigned char sm_raw[];
    uint32_t sbase = (s_u32(sm_raw) + 1023u) & ~1023u;
    asm volatile("" : "+r"(sbase));
    const uint32_t t0 = now_ns();
    const int t = threadIdx.x, lane = t & 31;
    {
        const uint32_t b = blockIdx.x, ut = threadIdx.x;
        const uint32_t off = (320 * (b & 1) + ((ut >> 2) & 96) + ((ut >> 4) & 7)) * 8192 + (b >> 1) * 256 + (ut & 15) * 16;
        const char* src = reinterpret_cast<const char*>(wq) + off;
        const uint32_t dst = sbase + OFF_WO + (ut >> 7) * 8192 + (ut & 8) * 512 + (ut & 112) * 8 + (((ut ^ (ut >> 4)) & 7) << 4);
        asm volatile("{.reg .pred p; setp.eq.u32 p, %2, 0;\n"
                     "@p cp.async.cg.shared.global [%0], [%1], 16;\n"
                     "@p cp.async.cg.shared.global [%0+1024], [%1+65536], 16;\n"
                     "@p cp.async.cg.shared.global [%0+2048], [%1+131072], 16;\n"
                     "@p cp.async.cg.shared.global [%0+3072], [%1+196608], 16;}"
                     :: "r"(dst), "l"(src), "r"((ut >> 9) | (b >> 6)) : "memory");
    }
    const int wb = __shfl_sync(0xffffffffu, (t >> 5) | (blockIdx.x << 8), 0);
    const int warp = wb & 255, r = (wb >> 8) & 1, id = (wb >> 9) & 31, me = 2 * id + r;
    const bool roleA = wb >> 14;
    const bool ffn = id < 27;
    const uint32_t bars = sbase + OFF_BAR, tb = bars + 8 * B_T;

    if (warp >= 16) {
        const int k = warp - 16;
        const u64 mapbase = reinterpret_cast<u64>(&prm.m[0]);
        if (lane == 0) {
            asm volatile("prefetch.tensormap [%0];" :: "l"(mapbase + 128 * (roleA ? 3 + k : k)) : "memory");
            if (k == 3) {
#pragma unroll
                for (int i = 0; i < B_T; ++i) asm volatile("mbarrier.init.shared::cta.b64 [%0], %1;" :: "r"(bars + 8 * i), "r"(i == B_W ? 32 : 1) : "memory");
                expect_tx(bars + 8 * B_X, roleA ? 2560 : 1280);
                asm volatile("cp.async.bulk.shared::cluster.global.mbarrier::complete_tx::bytes [%0], [%1], 1280, [%2];"
                             :: "r"(sbase + OFF_XS), "l"(prm.x), "r"(bars + 8 * B_X) : "memory");
                if (roleA) {
                    asm volatile("cp.async.bulk.shared::cluster.global.mbarrier::complete_tx::bytes [%0], [%1], 1280, [%2];"
                                 :: "r"(sbase + OFF_XS + 1280), "l"(prm.gw), "r"(bars + 8 * B_X) : "memory");
                    expect_tx(bars + 8 * B_EX2, 4096);
                }
                expect_tx(bars + 8 * B_EX0, roleA ? 4096 : 1024);
                expect_tx(bars + 8 * B_EX1, roleA ? 256 : 512);
            } else {
#pragma unroll
                for (int i = 0; i < 12; ++i)
                    asm volatile("mbarrier.init.shared::cta.b64 [%0], %1;" :: "r"(tb + 8 * (k + 3 * i)), "r"(i < 2 && !roleA && k + 3 * i < 4 ? 128 : 1) : "memory");
            }
            asm volatile("fence.mbarrier_init.release.cluster;" ::: "memory");
        }
        __syncwarp();
        asm volatile("barrier.cluster.arrive.relaxed.aligned;" ::: "memory");
        asm volatile("setmaxnreg.dec.sync.aligned.u32 32;");
        if (k == 3) {
            uint32_t tag;
            asm volatile("ld.relaxed.gpu.global.u32 %0, [%1];" : "=r"(tag) : "l"(&prm.scr->epoch) : "memory");
            tag = (tag & 1u) ^ 1u;
            if (roleA) {
                u64* const sdst = &prm.scr->sig[0][(lane & 30) + r][id][2 * (lane & 1)];
#pragma unroll
                for (int i = 0; i < 4; ++i) st_pkt2(sdst + i * (32 * 32 * 4), make_uint4(tag ^ 1u, 0u, tag ^ 1u, 0u));
                sts32(sbase + OFF_SMAX + 4 * lane, 0x80000000u);
                mbar_wait(bars + 8 * B_X);
                float s = 0.f;
#pragma unroll 2
                for (int i = 0; i < 10; ++i) {
                    const uint32_t xw = lds32(sbase + OFF_XS + (lane + 32 * i) * 4), gv = lds32(sbase + OFF_XS + 1280 + (lane + 32 * i) * 4);
                    uint32_t pr;
                    asm("mul.rn.bf16x2 %0, %1, %2;" : "=r"(pr) : "r"(xw), "r"(gv));
                    s += bf_lo(pr) + bf_hi(pr);
                }
#pragma unroll
                for (int j = 16; j > 0; j >>= 1) s += shx(s, j);
                const float ga = bf_round(__fdividef(1.0f, 1.0f + __expf(-bf_round(s))));
                if (lane == 0) sts128(sbase + OFF_EX0, make_uint4(__float_as_uint(ga), __float_as_uint(bf_round(1.0f - ga)), 0xffff0000u, 0u));
                asm volatile("bar.arrive %0, 416;" :: "r"(BAR_Q) : "memory");
                asm volatile("bar.arrive %0, 416;" :: "r"(BAR_Q + 1) : "memory");
                mbar_wait2(bars + 8 * B_EX0, bars + 8 * B_EX2);
                const uint32_t ts = now_ns();
                st_pkt2(sdst, make_uint4(tag, ts, tag, ts));
                st_pkt2(sdst + 32 * 32 * 4, make_uint4(tag, ts, tag, ts));
                bar_sync(BAR_L, 288);
#pragma unroll
                for (int i = 0; i < 2; ++i) {
                    const uint32_t la = sbase + OFF_LSUM + ((lane & 1) * 128 + 16 * i + (lane >> 1)) * 4;
                    float l = (ldsf(la) + ldsf(la + 128)) + (ldsf(la + 256) + ldsf(la + 384));
                    const uint32_t mw = lds32(sbase + OFF_SMAX + 4 * (16 * i + (lane >> 1)));
                    l += shx(l, 1);
                    const uint32_t lw = tag_word(__float_as_uint(l), tag);
                    st_pkt2(sdst + (2 + i) * (32 * 32 * 4), make_uint4(lw, mw, lw, mw));
                }
                TLT(19, 608);
            } else {
                const u64* ssrc = &prm.scr->sig[0][me][lane][0];
                wait_until(t0, prm.ts);
                const uint32_t last = t0 + __reduce_max_sync(0xffffffffu, (int)(poll_pkt(ssrc, tag).y - t0));
                if (lane == 0) {
                    sts32(sbase + OFF_LSUM, last);
                    asm volatile("mbarrier.arrive.shared::cta.b64 _, [%0];" :: "r"(bars + 8 * B_EX2) : "memory");
                }
                while ((int)(now_ns() - last) < prm.ls) { }
                const uint2 sv = poll_pkt(ssrc + 64 * 32 * 4, tag);
                const float e = ex2(__int_as_float(f2ord((int)sv.y)) - __int_as_float(f2ord(__reduce_max_sync(0xffffffffu, (int)sv.y))));
                float lg = e * F(sv.x & ~1u);
#pragma unroll
                for (int j = 16; j > 0; j >>= 1) lg += shx(lg, j);
                sts32(sbase + OFF_SMAX + 4 * lane, __float_as_uint(__fdividef(e, lg)));
                asm volatile("mbarrier.arrive.shared::cta.b64 _, [%0];" :: "r"(bars + 8 * B_W) : "memory");
                TLT(19, 608);
            }
            return;
        }
        const int total = roleA ? (ffn ? A_END : A_W1) : P_END;
        const uint32_t tp = t0 + ((me * prm.ph) >> 6);
#define MONITOR()
#pragma unroll 1
        for (int i = roleA ? k : (k ? k + 3 : 6); i < total; i += 3) {
            const uint4 e = prm.tile[roleA][i];
            const uint32_t c0 = (e.z & 0xffffu) + (e.w & 255u) * id + ((e.w >> 8) & 255u) * r;
            const uint32_t c1 = (e.z >> 16) + 32 * (((e.w >> 16) & 255u) * id + (e.w >> 24) * r);
            if (i >= CAP) mbar_wait(tb + 8 * (i - CAP));
            if (!roleA && i >= P_WO && i < P_WO + 3) {
                asm volatile("barrier.cluster.wait.aligned;" ::: "memory");
                mbar_wait(bars + 8 * B_EX0);
            }
            if (lane == 0) expect_tx(tb + 8 * i, (e.x >> 24) << 10);
            while ((int)(now_ns() - tp) < (int)e.y) { MONITOR(); }
            if (lane == 0) {
                tma3d(sbase + (e.x & 0xfffffu), mapbase + 128 * ((e.x >> 20) & 7u), c1, c0, tb + 8 * i);
            }
            __syncwarp();
        }
        return;
    }

    asm volatile("setmaxnreg.inc.sync.aligned.u32 112;");
    Scratch* const scr = prm.scr;
    uint32_t epoch;
    asm volatile("ld.relaxed.gpu.global.u32 %0, [%1];" : "=r"(epoch) : "l"(&scr->epoch) : "memory");
    asm volatile("barrier.cluster.arrive.relaxed.aligned;" ::: "memory");
    asm volatile("barrier.cluster.wait.aligned;" ::: "memory");
    if (!roleA) asm volatile("cp.async.mbarrier.arrive.noinc.shared::cta.b64 [%0];" :: "r"(tb + 8 * (warp >> 2)) : "memory");
    const uint32_t tag = (epoch & 1u) ^ 1u;
    const int g = lane >> 2, tq = lane & 3;
    const uint32_t tsw = sbase + ((lane & 7) + (lane >> 4) * 8) * 128 + (((2 * (warp & 3) + ((lane >> 3) & 1)) ^ (lane & 7)) << 4);
    float d[16];
    const bool reducer = roleA && me >= 24;
    uint32_t* const odst = &scr->x4[warp + 16 * (tq >> 1)][roleA ? 64 + me : me][g + 8 * (tq & 1)];
    {
        const uint4 em = make_uint4(tag ^ 1u, 0u, tag ^ 1u, 0u);
        if (roleA) {
            if (PREW & 2) {
                u64* const xd = &scr->x2[2 * ((t & 127) >> 3) + r][id][16 * (warp >> 2) + 2 * (lane & 7)];
                st_pkt2(xd, em); st_pkt2(xd + 32 * 32 * 64, em);
            }
        } else if ((lane & 14) == 0) st_pkt(&scr->x1[me][4 * warp + 2 * tq + (lane >> 4)], tag ^ 1u, 0u);
        if (!roleA || ffn) {
            st_word(odst, tag ^ 1u);
            if (tq < 2 && warp < 8) st_word(odst + 32 * 128 * 16, tag ^ 1u);
        }
    }
    mbar_wait(bars + 8 * B_X);

    if (roleA) {
        uint32_t fa[64];
        const int wg = warp >> 2;
        const uint32_t sbar = bars + 8 * (wg ? B_EX2 : B_EX0);
#define PRELOAD() do { const uint32_t pb = tb + 8 * (A_C + 2 * (~wg & 2)); mbar_wait2(pb, pb + 8); mbar_wait2(pb + 16, pb + 24); \
        _Pragma("unroll") for (int ks = 0; ks < 8; ++ks) \
            ldsm4t(fa + 4 * ks, tsw + OFF_C + (wg >> 1) * 32768 + (wg & 1) * 4096 + (ks >> 1) * 8192 + (ks & 1) * 2048); } while (0)
        const int h0 = 4 * (warp - 8);
        const int hq = h0 + (lane >> 3);
        const u64* src = &scr->x1[2 * hq + r][2 * (lane & 7)];
        const uint32_t qa = sbase + OFF_Q + hq * 128 + (((lane ^ hq) & 7) << 4);
        uint4 v[4];
        if (warp < 8) {
            const uint32_t base = sbase + OFF_C + (warp >> 1) * 8192 + (16 * (warp & 1) + (lane & 7) + ((lane >> 3) & 1) * 8) * 128;
            const u64 qd = sdesc(sbase + OFF_Q);
            const uint32_t rdst = peer_addr(sbase + OFF_SREM + t * 16, r ^ 1), rbar = peer_addr(sbar, r ^ 1);
            pin(rdst); pin(rbar);
            zero16(d);
#pragma unroll
            for (int cp = 1; cp >= 0; --cp) {
                mbar_wait(tb + 8 * (A_C + 4 * (1 - cp) + (warp >> 1)));
#pragma unroll
                for (int k = 0; k < 8; ++k) ldsm4(fa + 32 * cp + 4 * k, base + cp * 32768 + (k >> 2) * 4096 + (((2 * (k & 3) + (lane >> 4)) ^ (lane & 7)) << 4));
            }
            TLT(1, 224);
            bar_sync(BAR_Q + wg, 416);
            TLT(2, 0);
            asm volatile("wgmma.fence.sync.aligned;" ::: "memory");
#pragma unroll
            for (int ks = 0; ks < 16; ++ks) wgmma_rs(d, fa + 4 * ks, qd + (ks >> 2) * 256 + (ks & 3) * 2);
            asm volatile("wgmma.commit_group.sync.aligned;" ::: "memory");
            asm volatile("wgmma.wait_group.sync.aligned 0;" ::: "memory");
#pragma unroll
            for (int i = 0; i < 2; ++i)
                asm volatile("st.async.shared::cluster.mbarrier::complete_tx::bytes.v4.b32 [%0], {%1,%2,%3,%4}, [%5];"
                             :: "r"(rdst + i * 4096), "r"(pack_bf(d[8 * i], d[8 * i + 1])), "r"(pack_bf(d[8 * i + 2], d[8 * i + 3])),
                                "r"(pack_bf(d[8 * i + 4], d[8 * i + 5])), "r"(pack_bf(d[8 * i + 6], d[8 * i + 7])), "r"(rbar) : "memory");
            TLT(3, 0);
            TLT(17, 128);
        } else {
            pin(src); pin(qa);
            wait_until(t0, prm.tq0);
#pragma unroll
            for (int k = 0; k < 3; ++k) v[k] = ld_pkt2(src + 16 * k);
            while ((int)(now_ns() - t0) < prm.tq) { }
            TLT(8, 256);
            v[3] = ld_pkt2(src + 48);
        }
        PRELOAD();
        if (warp >= 8) {
#pragma unroll 1
            for (int it = 0; it < SPIN_MAX; ++it) {
                if (__all_sync(0xffffffffu, fresh2(v[0], tag) && fresh2(v[1], tag) && fresh2(v[2], tag) && fresh2(v[3], tag))) break;
#pragma unroll
                for (int k = 0; k < 4; ++k) if (!fresh2(v[k], tag)) v[k] = ld_pkt2(src + 16 * k);
                TLT(20, 256);
            }
#pragma unroll
            for (int k = 0; k < 4; ++k) {
                v[k].x &= ~1u; v[k].z &= ~1u;
                sts128(qa + k * 4096, v[k]);
            }
            asm volatile("fence.proxy.async.shared::cta;" ::: "memory");
            asm volatile("bar.arrive %0, 416;" :: "r"(BAR_Q) : "memory");
            asm volatile("bar.arrive %0, 416;" :: "r"(BAR_Q + 1) : "memory");
            TLT(9, 256);
        }
        const bool b4 = lane & 16, b3 = lane & 8, b2 = lane & 4;
        const int myhead = 8 * (g >> 1) + 2 * tq + (g & 1);
        const u64 pd = sdesc(sbase + OFF_P);
        const uint32_t oa = sbase + OFF_OT + ((lane & 7) + (lane >> 4) * 8) * 528 + warp * 32 + ((lane >> 3) & 1) * 16;
        const int hh = (t & 127) >> 3;
        const uint32_t ob = sbase + OFF_OT + hh * 528 + wg * 128 + (lane & 7) * 16;
        u64* const xdst = &scr->x2[2 * hh + r][id][16 * wg + 2 * (lane & 7)];
        pin(oa); pin(ob); pin(xdst);
        float u[8];
        uint32_t pk[8];
        if (warp < 8) {
            mbar_wait(sbar);
            TLT(4, 0);
            TLT(18, 128);
#pragma unroll
            for (int i = 0; i < 2; ++i) {
                const uint4 o = lds128(sbase + OFF_SREM + t * 16 + i * 4096);
                d[8 * i] += bf_lo(o.x); d[8 * i + 1] += bf_hi(o.x); d[8 * i + 2] += bf_lo(o.y); d[8 * i + 3] += bf_hi(o.y);
                d[8 * i + 4] += bf_lo(o.z); d[8 * i + 5] += bf_hi(o.z); d[8 * i + 6] += bf_lo(o.w); d[8 * i + 7] += bf_hi(o.w);
            }
#pragma unroll
            for (int i = 0; i < 8; ++i) u[i] = fmaxf(d[4 * (i >> 1) + (i & 1)], d[4 * (i >> 1) + (i & 1) + 2]);
#pragma unroll
            for (int i = 0; i < 4; ++i) u[i] = fmaxf(b4 ? u[i + 4] : u[i], shx(b4 ? u[i] : u[i + 4], 16));
#pragma unroll
            for (int i = 0; i < 2; ++i) u[i] = fmaxf(b3 ? u[i + 2] : u[i], shx(b3 ? u[i] : u[i + 2], 8));
            asm volatile("red.shared.max.s32 [%0], %1;" :: "r"(sbase + OFF_SMAX + 4 * myhead),
                         "r"(f2ord(__float_as_int(fmaxf(b2 ? u[1] : u[0], shx(b2 ? u[0] : u[1], 4))))) : "memory");
            bar_sync(BAR_HALF, 256);
            TLT(13, 0);
#pragma unroll
            for (int j = 0; j < 4; ++j) {
                const uint2 mi = lds64(sbase + OFF_SMAX + 32 * j + 8 * tq);
                const float m0 = __int_as_float(f2ord((int)mi.x)), m1 = __int_as_float(f2ord((int)mi.y));
                pk[2 * j] = pack_bf(ex2(d[4 * j] - m0), ex2(d[4 * j + 1] - m1));
                pk[2 * j + 1] = pack_bf(ex2(d[4 * j + 2] - m0), ex2(d[4 * j + 3] - m1));
            }
            stsm4t(tsw + OFF_P + wg * 4096, pk);
            stsm4t(tsw + OFF_P + wg * 4096 + 2048, pk + 4);
            asm volatile("fence.proxy.async.shared::cta;" ::: "memory");
            asm volatile("bar.arrive %0, 512;" :: "r"(BAR_ALL) : "memory");
            const uint32_t hm = lds32(sbase + OFF_EX0 + 8);
#pragma unroll
            for (int j = 0; j < 4; ++j) {
                u[2 * j] = F((pk[2 * j] << 16) & hm) + bf_lo(pk[2 * j + 1]);
                u[2 * j + 1] = F(pk[2 * j] & hm) + bf_hi(pk[2 * j + 1]);
            }
#pragma unroll
            for (int i = 0; i < 4; ++i) u[i] = (b4 ? u[i + 4] : u[i]) + shx(b4 ? u[i] : u[i + 4], 16);
#pragma unroll
            for (int i = 0; i < 2; ++i) u[i] = (b3 ? u[i + 2] : u[i]) + shx(b3 ? u[i] : u[i + 2], 8);
            sts32(sbase + OFF_LSUM + (warp * 32 + myhead) * 4, __float_as_uint((b2 ? u[1] : u[0]) + shx(b2 ? u[0] : u[1], 4)));
            zero16(d);
            bar_sync(BAR_L, 288);
        } else {
            zero16(d);
            bar_sync(BAR_ALL, NCOMP);
        }
        TLT(5, 256);
        asm volatile("wgmma.fence.sync.aligned;" ::: "memory");
#pragma unroll
        for (int ks = 0; ks < 8; ++ks) wgmma_rs(d, fa + 4 * ks, pd + (ks >> 2) * 256 + (ks & 3) * 2);
        asm volatile("wgmma.commit_group.sync.aligned;" ::: "memory");
        asm volatile("wgmma.wait_group.sync.aligned 0;" ::: "memory");
        {
            uint32_t ok[8];
#pragma unroll
            for (int i = 0; i < 8; ++i) ok[i] = pack_bf(d[2 * i], d[2 * i + 1]);
            stsm4t(oa, ok);
            stsm4t(oa + 16 * 528, ok + 4);
            bar_sync(BAR_WG + wg, 128);
            TLT(14, 128);
#pragma unroll
            for (int i = 0; i < 2; ++i) {
                uint4 v = lds128(ob + i * 16 * 528);
                v.x = tag_word(v.x, tag); v.z = tag_word(v.z, tag);
                st_pkt2(xdst + i * (32 * 32 * 64), v);
            }
        }
        TLT(6, 128);
    }

    if (roleA ? (ffn && warp < 4) : warp < 8) {
        uint32_t xa = sbase + OFF_XS + 640 * r + (lane >> 3) * 16;
        uint32_t wa = tsw + (roleA ? OFF_W1 : OFF_WO + (warp >> 2) * 4096);
        const uint32_t bar = tb + 8 * (roleA ? A_W1 : P_WQ);
        const int col = 16 * warp + g + 8 * (tq & 1);
        const uint32_t rank = roleA ? warp >> 1 : tq >> 1;
        const uint32_t rdst = peer_addr(sbase + (roleA ? OFF_EX1 + (r * 32 + (col & 31)) * 4 : OFF_EX0 + (r * 128 + col) * 4), rank);
        const uint32_t rbar = peer_addr(bars + 8 * (roleA ? B_EX1 : B_EX0), rank);
        pin(rdst); pin(rbar);
        zero16(d);
#pragma unroll 1
        for (int kb = 0; kb < 10; ++kb) {
            uint32_t b[4], a[8];
            ldsm4(b, xa);
            mbar_wait(bar + 8 * (kb >> (roleA ? 1 : 0)));
            ldsm4t(a, wa); ldsm4t(a + 4, wa + 2048);
            mma_w(d, a, b[0], b[1]); mma_w(d + 4, a + 4, b[2], b[3]);
            xa += 64; wa += roleA ? 4096 : 8192;
        }
        const float v = (tq & 1) ? d[2] + d[6] : d[0] + d[4];
        if (!roleA || tq < 2) st_async1(rdst, v, rbar);
    }

    if (!roleA) {
        TLT(1, 0);
        {
            const uint32_t base = sbase + OFF_WUK + (warp >> 1) * 8192 + ((warp & 1) * 16 + (lane & 7) + ((lane >> 3) & 1) * 8) * 128;
            u64* const qdst = &scr->x1[me][4 * warp + 2 * tq + (lane >> 4)];
            pin(base); pin(qdst);
            mbar_wait(bars + 8 * B_EX0);
            const uint4 q0 = lds128(sbase + OFF_EX0 + lane * 16), q1 = lds128(sbase + OFF_EX0 + 512 + lane * 16);
            const uint32_t w0 = pack_bf(F(q0.x) + F(q1.x), F(q0.y) + F(q1.y)), w1 = pack_bf(F(q0.z) + F(q1.z), F(q0.w) + F(q1.w));
            sts64(sbase + OFF_O + lane * 8, w0, w1);
            __syncwarp();
            uint32_t b[16];
#pragma unroll
            for (int k = 0; k < 4; ++k) ldsm4(b + 4 * k, sbase + OFF_O + (lane >> 3) * 16 + 64 * k);
            TLT(2, 0);
            zero16(d);
            mbar_wait(tb + 8 * (P_WUK + (warp >> 1)));
            uint32_t a[32];
#pragma unroll
            for (int k = 0; k < 8; ++k) ldsm4(a + 4 * k, base + (k >> 2) * 4096 + (((2 * (k & 3) + (lane >> 4)) ^ (lane & 7)) << 4));
#pragma unroll
            for (int k = 0; k < 8; ++k) mma_w(d + 4 * (k & 3), a + 4 * k, b[2 * k], b[2 * k + 1]);
            const float sc = 0.08838834764831845f * 1.4426950408889634f;
            const float v = ((tq & 1) ? (d[2] + d[6]) + (d[10] + d[14]) : (d[0] + d[4]) + (d[8] + d[12])) * sc;
            const uint32_t w = pack_bf(v, __shfl_down_sync(0xffffffffu, v, 4));
            const uint32_t w2 = __shfl_down_sync(0xffffffffu, w, 8);
            if ((lane & 14) == 0) st_pkt(qdst, tag_word(w, tag), w2);
        }
        TLT(3, 480);
        {
            uint32_t a[32];
            const int a0 = 4 * (warp >> 1);
            const u64* src = &scr->x2[me][a0][32 * (warp & 1) + lane];
            const uint32_t rank = (warp >> 2) & 1;
            const uint32_t rdst = peer_addr(sbase + OFF_EX1 + (2 * r + (warp >> 3)) * 144 + (16 * (warp & 3) + g + 8 * (tq & 1)) * 2, rank);
            const uint32_t rbar = peer_addr(bars + 8 * B_EX1, rank);
            const uint32_t ow = sbase + OFF_O + (warp >> 1) * 528 + (warp & 1) * 256 + lane * 8;
            const uint32_t ol = sbase + OFF_O + (lane & 7) * 528 + (warp >> 3) * 256 + (lane >> 3) * 16;
            const uint32_t wm = tsw + OFF_WO + (warp >> 3) * 16384 + rank * 4096, ob_ = tb + 8 * (P_WO + 2 * (warp >> 3));
            const uint32_t cl = sbase + OFF_EX1 + (lane & 3) * 144 + (lane >> 3) * 16;
            pin(src); pin(rdst); pin(rbar); pin(ow); pin(ol); pin(wm); pin(cl); pin(odst);
            const uint32_t ub = tb + 8 * (P_WUV + 4 * (warp >> 3));
            mbar_wait2(ub, ub + 8); mbar_wait2(ub + 16, ub + 24);
#pragma unroll
            for (int k = 0; k < 8; ++k) ldsm4t(a + 4 * k, tsw + OFF_WUV + (warp >> 3) * 32768 + rank * 4096 + (k >> 1) * 8192 + (k & 1) * 2048);
            zero16(d);
            mbar_wait(bars + 8 * B_EX2);
            TLT(4, 0);
            const uint32_t last = lds32(sbase + OFF_LSUM);
            while ((int)(now_ns() - last) < prm.lb) { }
            TLT(14, 0);
            uint2 v[4];
#pragma unroll
            for (int i = 0; i < 4; ++i) v[i] = ld_pkt(src + 64 * i);
            uint32_t w0[16], early;
            asm volatile("{.reg .pred p, q; mbarrier.test_wait.parity.shared::cta.b64 p, [%1], 0; mbarrier.test_wait.parity.shared::cta.b64 q, [%1+8], 0;"
                         " and.pred p, p, q; selp.u32 %0, 1, 0, p;}" : "=r"(early) : "r"(ob_) : "memory");
            early = __all_sync(0xffffffffu, early);
#define LOAD_WO(dst_, i_) do { _Pragma("unroll") for (int k = 0; k < 4; ++k) ldsm4t((dst_) + 4 * k, wm + (i_) * 32768 + (k >> 1) * 8192 + (k & 1) * 2048); } while (0)
            if (early) LOAD_WO(w0, 0);
            mbar_wait(bars + 8 * B_W);
            const uint4 wq4 = lds128(sbase + OFF_SMAX + 4 * a0);
            const float wn[4] = {F(wq4.x), F(wq4.y), F(wq4.z), F(wq4.w)};
#pragma unroll 1
            for (int it = 0; it < SPIN_MAX; ++it) {
                if (__all_sync(0xffffffffu, (((v[0].x ^ tag) | (v[1].x ^ tag) | (v[2].x ^ tag) | (v[3].x ^ tag)) & 1u) == 0)) break;
#pragma unroll
                for (int i = 0; i < 4; ++i) if ((v[i].x ^ tag) & 1u) v[i] = ld_pkt(src + 64 * i);
                TLT(20, 0);
            }
            TLT(5, 0);
            float c[4] = {0.f, 0.f, 0.f, 0.f};
#pragma unroll
            for (int i = 0; i < 4; ++i) {
                c[0] = fmaf(wn[i], bf_lo(v[i].x & ~1u), c[0]); c[1] = fmaf(wn[i], bf_hi(v[i].x), c[1]);
                c[2] = fmaf(wn[i], bf_lo(v[i].y), c[2]); c[3] = fmaf(wn[i], bf_hi(v[i].y), c[3]);
            }
            sts64(ow, pack_bf(c[0], c[1]), pack_bf(c[2], c[3]));
            bar_sync(BAR_ALL, NCOMP);
            TLT(6, 0);
            uint32_t b[16];
#pragma unroll
            for (int k = 0; k < 4; ++k) ldsm4(b + 4 * k, ol + 64 * k);
#pragma unroll
            for (int k = 0; k < 8; ++k) mma_w(d + 4 * (k & 3), a + 4 * k, b[2 * k], b[2 * k + 1]);
            const float c0 = ((d[0] + d[1]) + (d[4] + d[5])) + ((d[8] + d[9]) + (d[12] + d[13]));
            const float c1 = ((d[2] + d[3]) + (d[6] + d[7])) + ((d[10] + d[11]) + (d[14] + d[15]));
            float v_ = ((tq & 1) ? c1 : c0) + shx((tq & 1) ? c0 : c1, 1);
            v_ += shx(v_, 2);
            const float vn = __shfl_down_sync(0xffffffffu, v_, 4);
            if ((lane & 6) == 0)
                asm volatile("st.async.shared::cluster.mbarrier::complete_tx::bytes.b32 [%0], %1, [%2];" :: "r"(rdst), "r"(pack_bf(v_, vn)), "r"(rbar) : "memory");
            TLT(15, 0);
            if (!early) { mbar_wait2(ob_, ob_ + 8); LOAD_WO(w0, 0); }
            mbar_wait2(ob_ + 32, ob_ + 40);
            LOAD_WO(a, 1);
            uint32_t late = 0;
            if (warp < 8) {
                asm volatile("{.reg .pred p, q; mbarrier.test_wait.parity.shared::cta.b64 p, [%1], 0; mbarrier.test_wait.parity.shared::cta.b64 q, [%1+8], 0;"
                             " and.pred p, p, q; selp.u32 %0, 0, 1, p;}" : "=r"(late) : "r"(ob_ + 64) : "memory");
                late = __any_sync(0xffffffffu, late);
                if (!late) LOAD_WO(a + 16, 2);
            }
            zero16(d);
            mbar_wait(bars + 8 * B_EX1);
            TLT(7, 0);
            ldsm4(b, cl); ldsm4(b + 4, cl + 64);
#pragma unroll
            for (int k = 0; k < 4; ++k) {
                mma_w(d + 4 * (k & 1), w0 + 4 * k, b[2 * k], b[2 * k + 1]);
                mma_w(d + 8 + 4 * (k & 1), a + 4 * k, b[2 * k], b[2 * k + 1]);
            }
            {
                const float lo = tq < 2 ? (d[0] + d[1]) + (d[4] + d[5]) : (d[8] + d[9]) + (d[12] + d[13]);
                const float hi = tq < 2 ? (d[2] + d[3]) + (d[6] + d[7]) : (d[10] + d[11]) + (d[14] + d[15]);
                st_word(odst, tag_word(__float_as_uint(((tq & 1) ? hi : lo) + shx((tq & 1) ? lo : hi, 1)), tag));
            }
            if (warp < 8) {
                if (late) { mbar_wait2(ob_ + 64, ob_ + 72); LOAD_WO(a + 16, 2); }
                zero16(d);
#pragma unroll
                for (int k = 0; k < 4; ++k) mma_w(d + 4 * k, a + 16 + 4 * k, b[2 * k], b[2 * k + 1]);
                const float lo = ((d[0] + d[1]) + (d[4] + d[5])) + ((d[8] + d[9]) + (d[12] + d[13]));
                const float hi = ((d[2] + d[3]) + (d[6] + d[7])) + ((d[10] + d[11]) + (d[14] + d[15]));
                const float o = ((tq & 1) ? hi : lo) + shx((tq & 1) ? lo : hi, 1);
                if (tq < 2) st_word(odst + 32 * 128 * 16, tag_word(__float_as_uint(o), tag));
            }
        }
    } else if (ffn) {
        mbar_wait(bars + 8 * B_EX1);
        const uint32_t ep = sbase + OFF_EX1 + (lane & 15) * 8;
        const uint2 e0 = lds64(ep), e1 = lds64(ep + 128);
        const float h0 = bf_round(F(e0.x) + F(e1.x)), h1 = bf_round(F(e0.y) + F(e1.y));
        const uint32_t w = pack_bf(__fdividef(h0, 1.0f + __expf(-h0)), __fdividef(h1, 1.0f + __expf(-h1)));
        uint32_t bv[4];
#pragma unroll
        for (int i = 0; i < 4; ++i) bv[i] = __shfl_sync(0xffffffffu, w, 4 * i + tq);
        const uint32_t wm = tsw + OFF_W2 + (warp >> 2) * 4096, wb_ = tb + 8 * (A_W2 + (warp >> 3));
        uint32_t a[16];
        mbar_wait2(wb_, wb_ + 16);
        ldsm4t(a, wm); ldsm4t(a + 4, wm + 2048); ldsm4t(a + 8, wm + 16384); ldsm4t(a + 12, wm + 18432);
        zero16(d);
        mma_w(d, a, bv[0], bv[1]); mma_w(d + 4, a + 4, bv[2], bv[3]);
        mma_w(d + 8, a + 8, bv[0], bv[1]); mma_w(d + 12, a + 12, bv[2], bv[3]);
        st_word(odst, tag_word(__float_as_uint(tq == 0 ? d[0] + d[4] : (tq == 1 ? d[2] + d[6] : (tq == 2 ? d[8] + d[12] : d[10] + d[14]))), tag));
        if (warp < 8) {
            mbar_wait(wb_ + 32);
            ldsm4t(a, wm + 32768); ldsm4t(a + 4, wm + 34816);
            zero16(d);
            mma_w(d, a, bv[0], bv[1]); mma_w(d + 4, a + 4, bv[2], bv[3]);
            if (tq < 2) st_word(odst + 32 * 128 * 16, tag_word(__float_as_uint(tq ? d[2] + d[6] : d[0] + d[4]), tag));
        }
    }
    TLT(10, 0);
    if (reducer) {
        const uint32_t* rsrc = &scr->x4[me - 24][8 * warp][4 * lane];
        const uint32_t rw = sbase + OFF_O + (warp * 16 + 4 * tq + ((lane >> 3) & 2) + ((lane >> 3) & 1)) * 4;
        const uint32_t rp = sbase + OFF_O + ((lane >> 4) * 128 + (lane & 15)) * 4;
        __nv_bfloat16* const op = prm.out + 16 * (me - 24) + (lane & 15);
        const float gg = ldsf(sbase + OFF_EX0 + (warp >> 3) * 4);
        pin(rw); pin(rp); pin(op);
        uint4 rv = make_uint4(tag, tag, tag, tag);
        if (t < 118 * 4) rv.x ^= 1u;
#pragma unroll 1
        for (int it = 0; it < SPIN_MAX; ++it) {
            const bool ok = (((rv.x ^ tag) | (rv.y ^ tag) | (rv.z ^ tag) | (rv.w ^ tag)) & 1u) == 0;
            if (__all_sync(0xffffffffu, ok)) break;
            if (!ok) rv = ld_word4(rsrc);
        }
        const bool b4 = lane & 16, b3 = lane & 8;
        const float o0 = F(rv.x & ~1u), o1 = F(rv.y & ~1u), o2 = F(rv.z & ~1u), o3 = F(rv.w & ~1u);
        const float y0 = (b4 ? o2 : o0) + shx(b4 ? o0 : o2, 16), y1 = (b4 ? o3 : o1) + shx(b4 ? o1 : o3, 16);
        float y = (b3 ? y1 : y0) + shx(b3 ? y0 : y1, 8);
        y += shx(y, 4);
        if (!(lane & 4)) sts32(rw, __float_as_uint(gg * y));
        if (warp != 15) asm volatile("bar.arrive %0, 512;" :: "r"(BAR_Q) : "memory");
        else {
            bar_sync(BAR_Q, NCOMP);
            float z = ((ldsf(rp) + ldsf(rp + 64)) + (ldsf(rp + 128) + ldsf(rp + 192))) + ((ldsf(rp + 256) + ldsf(rp + 320)) + (ldsf(rp + 384) + ldsf(rp + 448)));
            z += shx(z, 16);
            if (lane < 16) *op = __float2bfloat16_rn(z);
            if (me == 24 && lane == 0) asm volatile("st.relaxed.gpu.global.u32 [%0], %1;" :: "l"(&scr->epoch), "r"(epoch + 1u) : "memory");
            TLT(11, 480);
        }
    }
}

typedef CUresult (*EncodeFn)(CUtensorMap*, CUtensorMapDataType, cuuint32_t, void*, const cuuint64_t*, const cuuint64_t*,
                             const cuuint32_t*, const cuuint32_t*, CUtensorMapInterleave, CUtensorMapSwizzle,
                             CUtensorMapL2promotion, CUtensorMapFloatOOBfill);

void make_map(EncodeFn enc, CUtensorMap* m, void* base, uint64_t cols, uint64_t rows, uint32_t brows, uint32_t bblk) {
    cuuint64_t dims[3] = {64, rows, cols / 64};
    cuuint64_t strides[2] = {cols * 2, 128};
    cuuint32_t box[3] = {64, brows, bblk};
    cuuint32_t es[3] = {1, 1, 1};
    enc(m, CU_TENSOR_MAP_DATA_TYPE_BFLOAT16, 3, base, dims, strides, box, es, CU_TENSOR_MAP_INTERLEAVE_NONE,
        CU_TENSOR_MAP_SWIZZLE_128B, CU_TENSOR_MAP_L2_PROMOTION_NONE, CU_TENSOR_MAP_FLOAT_OOB_FILL_NONE);
}

}

extern "C" void kernel_launch(void* const* d_in, const int* in_sizes, int n_in, void* d_out, int out_size) {
    (void)in_sizes; (void)n_in; (void)out_size;
    static EncodeFn enc = nullptr;
    static void* scr = nullptr;
    if (!enc) {
        cudaFuncSetAttribute(fused_kernel, cudaFuncAttributeMaxDynamicSharedMemorySize, SMEM_BYTES);
        cudaGetSymbolAddress(&scr, g_scr);
        void* fn = nullptr;
        cudaDriverEntryPointQueryResult qr;
        cudaGetDriverEntryPoint("cuTensorMapEncodeTiled", &fn, cudaEnableDefault, &qr);
        enc = (EncodeFn)fn;
    }
    Params prm;
    prm.x = (const __nv_bfloat16*)d_in[0];
    prm.gw = (const __nv_bfloat16*)d_in[9];
    prm.out = (__nv_bfloat16*)d_out;
    prm.scr = (Scratch*)scr;
    const Tune tn = tune();
    prm.tq0 = tn.TQ0; prm.tq = tn.TQ; prm.ts = tn.TS; prm.lb = tn.LB; prm.ls = tn.LS; prm.ph = tn.PH;
    for (int i = 0; i < 36; ++i) {
        auto mk = [&](int dst, int map, int kb, int when, int blk, int row, int blki, int blkr, int rowi, int rowr) {
            if (map == 2 || map == 3 || map >= 5) {
                const int v = when - tn.T3, a = v < tn.V1 ? v : tn.V1, c = v > tn.V2 ? v - tn.V2 : 0, b = v - a - c;
                when = tn.T3 + (a * tn.S1 + b * tn.S2 + c * tn.S3) / 100;
                if (map < 4 && when > TV(PP0, 100000)) when += TV(PPL, 0);
                if (map == 6 && TV(TW2, 0)) when = TV(TW2, 0) + (i - A_W2) * TV(DW2, 100);
            }
            if ((TV(NOLOAD, 0) >> map) & 1) kb = 0;
            return make_uint4(dst | map << 20 | kb << 24, when, blk | row << 16, blki | blkr << 8 | rowi / 32 << 16 | rowr / 32 << 24);
        };
        const int j = i - P_WO, f = i - A_W2;
        prm.tile[0][i] = i < P_WUK ? mk(OFF_WO + i * 8192, 0, 8, tn.TP1 + (i - 17) * tn.DD1, 0, 32 * i, 2, 0, 0, 320)
                       : i < P_WUV ? mk((i - P_WUK) * 8192, 1, 8, tn.TP1 + (i - 17) * tn.DD1, 0, 32 * (i - P_WUK), 2, 0, 0, 256)
                       : i < P_WO  ? mk((i - P_WUK) * 8192, 2, 8, tn.T3 + (i - P_WUV) * tn.DP2, 0, 32 * (i - P_WUV), 2, 0, 0, 256)
                                   : mk(OFF_WO + j * 8192, 3, 8, tn.T3 + 8 * tn.DP2 + j * tn.DP3, j & ~1, 32 * (j & 1), 0, 0, 128, 64);
        prm.tile[1][i] = i < A_W1 ? mk(((i ^ 4) & 7) * 8192, 4, 8, tn.TA1 + i * tn.DA1, i < 4 ? 2 : 0, 32 * (i & 3), 0, 4, 128, 0)
                       : i < A_W2 ? mk(i * 8192, 5, 8, tn.T3 + (i - A_W1) * tn.DA2, 0, 64 * (i - A_W1), 1, 0, 0, 320)
                                  : mk(OFF_W2 + f * 8192, 6, 8, tn.T3 + (5 + f) * tn.DA2, 2 * f, 0, 0, 0, 64, 32);
    }
    make_map(enc, &prm.m[0], d_in[2], 4096, MD, 32, 2);
    make_map(enc, &prm.m[1], d_in[3], 4096, DC, 32, 2);
    make_map(enc, &prm.m[2], d_in[4], 4096, DC, 32, 2);
    make_map(enc, &prm.m[3], d_in[5], MD, 4096, 32, 2);
    make_map(enc, &prm.m[4], d_in[1], DC, SK, 32, 2);
    make_map(enc, &prm.m[5], d_in[7], FF, MD, 64, 1);
    make_map(enc, &prm.m[6], d_in[8], MD, FF, 32, 2);
    fused_kernel<<<NCTA, NTHREADS, SMEM_BYTES>>>((const __nv_bfloat16*)d_in[2], prm);
}
```

```cpp
#include <cuda_runtime.h>
#include <cuda_bf16.h>
#include <cuda.h>
#include <stdint.h>
#include <stdlib.h>

namespace {

typedef unsigned long long u64;
constexpr int MD = 640, DC = 512, SK = 4096, FF = 1728;
constexpr int NCTA = 128;
constexpr int NCOMP = 512;
constexpr int NTHREADS = NCOMP + 128;
constexpr int SPIN_MAX = 1 << 20;

struct Tune { int DD, TP1, DD1, TA1, DA1, T3, DP2, DA2, DP3, TQ0, TQ, TS, LB, LS, PH, V1, V2, S1, S2, S3; };
#define TV(n, d) (d)
static Tune tune() {
    Tune t;
    t.DD = TV(DD, 168);
    t.DD1 = TV(DD1, 170);
    t.TP1 = TV(TP1, 2360);
    t.TA1 = TV(TA1, 2680);
    t.DA1 = TV(DA1, 135);
    t.T3 = TV(T3, 4140);
    t.DP2 = TV(DP2, 236);
    t.DA2 = TV(DA2, 385);
    t.DP3 = TV(DP3, 186);
    t.TQ = TV(TQ, 4580);
    t.TS = TV(TS, 6400);
    t.LB = TV(LB, 1940);
    t.LS = TV(LS, 1650);
    t.TQ0 = TV(TQ0, 4380);
    t.PH = TV(PH, 200);
    t.V1 = TV(V1, 2000); t.V2 = TV(V2, 3200); t.S1 = TV(S1, 100); t.S2 = TV(S2, 100); t.S3 = TV(S3, 100);
    return t;
}
#define CAP 15
#define PREW 7
#define TWO 1
#define PRE 1
#define ROLEMIX 2

constexpr int OFF_WUK = 0, OFF_WUV = 65536, OFF_WO = 131072;
constexpr int OFF_C = 0, OFF_W1 = 65536, OFF_W2 = OFF_W1 + 40960;
constexpr int OFF_Q = OFF_W2 + 57344, OFF_PIN = OFF_Q + 16384, OFF_POWN = OFF_PIN + 5120,
              OFF_SREM = OFF_POWN + 5120, OFF_OT = OFF_SREM + 4096;
constexpr int OFF_XS = 212992;
constexpr int OFF_EX0 = OFF_XS + 2560;
constexpr int OFF_EX1 = OFF_EX0 + 1024;
constexpr int OFF_O = OFF_EX1 + 1024;
constexpr int OFF_SMAX = OFF_O + 4224;
constexpr int OFF_LSUM = OFF_SMAX + 256;
constexpr int OFF_TL = OFF_LSUM + 1024;
constexpr int OFF_BAR = OFF_TL + 256;
enum { B_X = 0, B_EX0 = 1, B_EX1 = 2, B_EX2 = 3, B_W = 4, B_M = 5, B_T = 6, B_COUNT = B_T + 36 };
constexpr int SMEM_BYTES = OFF_BAR + B_COUNT * 8 + 1024;
static_assert(SMEM_BYTES <= 232448, "smem");
enum { P_WQ = 0, P_WUK = 10, P_WUV = 18, P_WO = 26, P_END = 36, A_C = 0, A_W1 = 8, A_W2 = 13, A_END = 20 };
static_assert(OFF_OT + 32 * 528 <= OFF_XS, "A layout");

struct Scratch {
    u64 x1[64][64];
    uint32_t x4[40][64][16];
    uint32_t xh[FF];
    u64 x2[64][32][64];
    u64 st[2][64][32][2];
    unsigned int epoch;
};
__device__ Scratch g_scr;

struct Params {
    const __nv_bfloat16* x;
    const __nv_bfloat16* gw;
    __nv_bfloat16* out;
    Scratch* scr;
    int tq0, tq, ts, lb, ls, ph, skew, tr, tr1, prew, tend;
    uint4 tile[2][36];
    CUtensorMap m[7];
};

#define TLT(i, th)

__device__ __forceinline__ uint32_t s_u32(const void* p) { return (uint32_t)__cvta_generic_to_shared(p); }
__device__ __forceinline__ float bf_lo(uint32_t w) { return __uint_as_float(w << 16); }
__device__ __forceinline__ float bf_hi(uint32_t w) { return __uint_as_float(w & 0xffff0000u); }
__device__ __forceinline__ float bf_round(float v) { return __bfloat162float(__float2bfloat16_rn(v)); }
__device__ __forceinline__ uint32_t pack_bf(float lo, float hi) {
    uint32_t r; asm("cvt.rn.bf16x2.f32 %0, %1, %2;" : "=r"(r) : "f"(hi), "f"(lo)); return r;
}
__device__ __forceinline__ float ex2(float v) { float r; asm("ex2.approx.ftz.f32 %0, %1;" : "=f"(r) : "f"(v)); return r; }
__device__ __forceinline__ uint32_t tag_word(uint32_t w, uint32_t tag) { return (w & ~1u) | tag; }
__device__ __forceinline__ void pin(uint32_t v) { asm volatile("{.reg .pred p; setp.eq.u32 p, %0, 0xfffffff1; @p st.shared.u32 [%0], %0;}" :: "r"(v) : "memory"); }
__device__ __forceinline__ void pin(const void* v) { asm volatile("{.reg .pred p; setp.eq.u64 p, %0, 1; @p st.global.u32 [%0], 0;}" :: "l"(v) : "memory"); }
__device__ __forceinline__ uint32_t lds32(uint32_t a) { uint32_t v; asm volatile("ld.shared.u32 %0, [%1];" : "=r"(v) : "r"(a) : "memory"); return v; }
__device__ __forceinline__ float ldsf(uint32_t a) { return __uint_as_float(lds32(a)); }
__device__ __forceinline__ uint2 lds64(uint32_t a) { uint2 v; asm volatile("ld.shared.v2.u32 {%0,%1}, [%2];" : "=r"(v.x), "=r"(v.y) : "r"(a) : "memory"); return v; }
__device__ __forceinline__ uint4 lds128(uint32_t a) {
    uint4 v; asm volatile("ld.shared.v4.u32 {%0,%1,%2,%3}, [%4];" : "=r"(v.x), "=r"(v.y), "=r"(v.z), "=r"(v.w) : "r"(a) : "memory"); return v;
}
__device__ __forceinline__ void sts32(uint32_t a, uint32_t v) { asm volatile("st.shared.u32 [%0], %1;" :: "r"(a), "r"(v) : "memory"); }
__device__ __forceinline__ void sts64(uint32_t a, uint32_t x, uint32_t y) { asm volatile("st.shared.v2.u32 [%0], {%1,%2};" :: "r"(a), "r"(x), "r"(y) : "memory"); }
__device__ __forceinline__ void sts128(uint32_t a, const uint4& v) {
    asm volatile("st.shared.v4.u32 [%0], {%1,%2,%3,%4};" :: "r"(a), "r"(v.x), "r"(v.y), "r"(v.z), "r"(v.w) : "memory");
}
#define F(x) __uint_as_float(x)

__device__ __forceinline__ void st_pkt(u64* p, uint32_t lo, uint32_t hi) {
    asm volatile("{.reg .b64 v; mov.b64 v, {%1,%2}; st.relaxed.gpu.global.b64 [%0], v;}" :: "l"(p), "r"(lo), "r"(hi) : "memory");
}
__device__ __forceinline__ void st_word(uint32_t* p, uint32_t v) { asm volatile("st.relaxed.gpu.global.u32 [%0], %1;" :: "l"(p), "r"(v) : "memory"); }
__device__ __forceinline__ uint4 ld_word4(const uint32_t* p) {
    uint4 v; asm volatile("ld.relaxed.gpu.global.v4.u32 {%0,%1,%2,%3}, [%4];" : "=r"(v.x), "=r"(v.y), "=r"(v.z), "=r"(v.w) : "l"(p) : "memory"); return v;
}
__device__ __forceinline__ uint2 ld_pkt(const u64* p) {
    uint2 v; asm volatile("{.reg .b64 v; ld.relaxed.gpu.global.b64 v, [%2]; mov.b64 {%0,%1}, v;}" : "=r"(v.x), "=r"(v.y) : "l"(p) : "memory"); return v;
}
__device__ __forceinline__ uint4 ld_pkt2(const u64* p) {
    uint4 v; asm volatile("{.reg .b64 a,b; ld.relaxed.gpu.global.v2.b64 {a,b}, [%4]; mov.b64 {%0,%1}, a; mov.b64 {%2,%3}, b;}"
                          : "=r"(v.x), "=r"(v.y), "=r"(v.z), "=r"(v.w) : "l"(p) : "memory"); return v;
}
__device__ __forceinline__ bool fresh4(const uint4& v, uint32_t tag) { return (((v.x ^ tag) | (v.y ^ tag) | (v.z ^ tag) | (v.w ^ tag)) & 1u) == 0; }
__device__ __forceinline__ bool fresh2(const uint4& v, uint32_t tag) { return (((v.x ^ tag) | (v.z ^ tag)) & 1u) == 0; }
__device__ __forceinline__ uint32_t now_ns() { uint32_t v; asm volatile("mov.u32 %0, %%globaltimer_lo;" : "=r"(v) :: "memory"); return v; }
__device__ __forceinline__ void wait_until(uint32_t t0, int when) {
    while ((int)(now_ns() - t0) < when - 400) __nanosleep(100);
    while ((int)(now_ns() - t0) < when) { }
}

__device__ __forceinline__ uint4 poll_pkt2(const u64* p, uint32_t tag) {
    uint4 s = ld_pkt2(p);
#pragma unroll 1
    for (int it = 0; it < SPIN_MAX && !__all_sync(0xffffffffu, fresh2(s, tag)); ++it) { __nanosleep(100); s = ld_pkt2(p); }
    return s;
}

__device__ __forceinline__ void mbar_wait(uint32_t bar) {
    asm volatile("{\n.reg .pred p;\nLW:\nmbarrier.try_wait.parity.shared::cta.b64 p, [%0], 0;\n@!p bra.uni LW;\n}" :: "r"(bar) : "memory");
}
__device__ __forceinline__ void mbar_wait2(uint32_t bar0, uint32_t bar1) {
    asm volatile("{\n.reg .pred p, q;\nLW:\nmbarrier.try_wait.parity.shared::cta.b64 p, [%0], 0;\n"
                 "mbarrier.try_wait.parity.shared::cta.b64 q, [%1], 0;\nand.pred p, p, q;\n@!p bra.uni LW;\n}" :: "r"(bar0), "r"(bar1) : "memory");
}
__device__ __forceinline__ void expect_tx(uint32_t bar, uint32_t bytes) {
    asm volatile("mbarrier.arrive.expect_tx.relaxed.cta.shared::cta.b64 _, [%0], %1;" :: "r"(bar), "r"(bytes) : "memory");
}
__device__ __forceinline__ void tma3d(uint32_t dst, u64 map, uint32_t row, uint32_t blk, uint32_t bar) {
    asm volatile("cp.async.bulk.tensor.3d.shared::cluster.global.mbarrier::complete_tx::bytes [%0], [%1, {%5, %2, %3}], [%4];"
                 :: "r"(dst), "l"(map), "r"(row), "r"(blk), "r"(bar), "r"(0) : "memory");
}
__device__ __forceinline__ void bar_sync(int id, int n) { asm volatile("bar.sync %0, %1;" :: "r"(id), "r"(n) : "memory"); }
__device__ __forceinline__ uint32_t peer_addr(uint32_t a, uint32_t rank) {
    uint32_t r; asm("mapa.shared::cluster.u32 %0, %1, %2;" : "=r"(r) : "r"(a), "r"(rank)); return r;
}
__device__ __forceinline__ void st_async1(uint32_t dst, float a, uint32_t bar) {
    asm volatile("st.async.shared::cluster.mbarrier::complete_tx::bytes.f32 [%0], %1, [%2];" :: "r"(dst), "f"(a), "r"(bar) : "memory");
}
__device__ __forceinline__ void ldsm4(uint32_t* r, uint32_t a) {
    asm volatile("ldmatrix.sync.aligned.m8n8.x4.shared.b16 {%0,%1,%2,%3}, [%4];"
                 : "=r"(r[0]), "=r"(r[1]), "=r"(r[2]), "=r"(r[3]) : "r"(a) : "memory");
}
__device__ __forceinline__ void ldsm4t(uint32_t* r, uint32_t a) {
    asm volatile("ldmatrix.sync.aligned.m8n8.x4.trans.shared.b16 {%0,%1,%2,%3}, [%4];"
                 : "=r"(r[0]), "=r"(r[1]), "=r"(r[2]), "=r"(r[3]) : "r"(a) : "memory");
}
__device__ __forceinline__ void mma_w(float* c, const uint32_t* a, uint32_t b0, uint32_t b1) {
    asm volatile("mma.sync.aligned.m16n8k16.row.col.f32.bf16.bf16.f32 {%0,%1,%2,%3}, {%4,%5,%6,%7}, {%8,%9}, {%0,%1,%2,%3};"
                 : "+f"(c[0]), "+f"(c[1]), "+f"(c[2]), "+f"(c[3]) : "r"(a[0]), "r"(a[1]), "r"(a[2]), "r"(a[3]), "r"(b0), "r"(b1));
}
#define WG_D "{%0,%1,%2,%3,%4,%5,%6,%7,%8,%9,%10,%11,%12,%13,%14,%15}"
#define WG_DREGS "+f"(d[0]), "+f"(d[1]), "+f"(d[2]), "+f"(d[3]), "+f"(d[4]), "+f"(d[5]), "+f"(d[6]), "+f"(d[7]), \
                 "+f"(d[8]), "+f"(d[9]), "+f"(d[10]), "+f"(d[11]), "+f"(d[12]), "+f"(d[13]), "+f"(d[14]), "+f"(d[15])
__device__ __forceinline__ void wgmma_rs(float* d, const uint32_t* a, u64 desc) {
    asm volatile("wgmma.mma_async.sync.aligned.m64n32k16.f32.bf16.bf16 " WG_D ", {%16,%17,%18,%19}, %20, 1, 1, 1, 0;"
                 : WG_DREGS : "r"(a[0]), "r"(a[1]), "r"(a[2]), "r"(a[3]), "l"(desc) : "memory");
}
__device__ __forceinline__ void wgmma_ss(float* d, u64 adesc, u64 desc) {
    asm volatile("wgmma.mma_async.sync.aligned.m64n32k16.f32.bf16.bf16 " WG_D ", %16, %17, 1, 1, 1, 0, 0;"
                 : WG_DREGS : "l"(adesc), "l"(desc) : "memory");
}
__device__ __forceinline__ void zero16(float* d) {
#pragma unroll
    for (int i = 0; i < 16; ++i) { d[i] = 0.f; asm volatile("" : "+f"(d[i])); }
}
__device__ __forceinline__ void stsm4t(uint32_t a, const uint32_t* r) {
    asm volatile("stmatrix.sync.aligned.m8n8.x4.trans.shared.b16 [%0], {%1,%2,%3,%4};" :: "r"(a), "r"(r[0]), "r"(r[1]), "r"(r[2]), "r"(r[3]) : "memory");
}
__device__ __forceinline__ void st_pkt2(u64* p, const uint4& v) {
    asm volatile("{.reg .b64 a,b; mov.b64 a, {%1,%2}; mov.b64 b, {%3,%4}; st.relaxed.gpu.global.v2.b64 [%0], {a,b};}"
                 :: "l"(p), "r"(v.x), "r"(v.y), "r"(v.z), "r"(v.w) : "memory");
}
__device__ __forceinline__ u64 sdesc(uint32_t addr) {
    return (u64)((addr & 0x3FFFFu) >> 4) | (1ull << 16) | (64ull << 32) | (1ull << 62);
}
__device__ __forceinline__ float shx(float v, int m) { return __shfl_xor_sync(0xffffffffu, v, m); }

constexpr int BAR_ALL = 1, BAR_HALF = 2, BAR_L = 4, BAR_WG = 5, BAR_Q = 9;
__device__ __forceinline__ void spin(uint32_t n) { const uint32_t c = clock(); while ((uint32_t)clock() - c < n) { } }
__device__ __forceinline__ int f2ord(int b) { return b ^ ((b >> 31) & 0x7fffffff); }

__global__ void __cluster_dims__(2, 1, 1) __launch_bounds__(NTHREADS, 1)
fused_kernel(const __nv_bfloat16* __restrict__ wq, const __grid_constant__ Params prm) {
    extern __shared__ __align__(1024) unsigned char sm_raw[];
    uint32_t sbase = (s_u32(sm_raw) + 1023u) & ~1023u;
    asm volatile("" : "+r"(sbase));
    const uint32_t t0 = now_ns();
    const int t = threadIdx.x, lane = t & 31;
    {
        const uint32_t b = blockIdx.x, ut = threadIdx.x;
        const uint32_t off = (320 * (b & 1) + ((ut >> 2) & 96) + ((ut >> 4) & 7)) * 8192 + (b >> 1) * 256 + (ut & 15) * 16;
        const char* src = reinterpret_cast<const char*>(wq) + off;
        const uint32_t dst = sbase + OFF_WO + (ut >> 7) * 8192 + (ut & 8) * 512 + (ut & 112) * 8 + (((ut ^ (ut >> 4)) & 7) << 4);
        asm volatile("{.reg .pred p; setp.eq.u32 p, %2, 0;\n"
                     "@p cp.async.cg.shared.global [%0], [%1], 16;\n"
                     "@p cp.async.cg.shared.global [%0+1024], [%1+65536], 16;\n"
                     "@p cp.async.cg.shared.global [%0+2048], [%1+131072], 16;\n"
                     "@p cp.async.cg.shared.global [%0+3072], [%1+196608], 16;}"
                     :: "r"(dst), "l"(src), "r"((ut >> 9) | (b >> 6)) : "memory");
    }
    const int wb = __shfl_sync(0xffffffffu, (t >> 5) | (blockIdx.x << 8), 0);
    const int warp = wb & 255, r = (wb >> 8) & 1, id = (wb >> 9) & 31, me = 2 * id + r;
    const bool roleA = wb >> 14;
    const bool ffn = id < 27;
    const uint32_t bars = sbase + OFF_BAR, tb = bars + 8 * B_T;

    if (warp >= 16) {
        const int k = warp - 16;
        const u64 mapbase = reinterpret_cast<u64>(&prm.m[0]);
        if (lane == 0) {
            asm volatile("prefetch.tensormap [%0];" :: "l"(mapbase + 128 * (roleA ? 3 + k : k)) : "memory");
            if (k == 3) {
#pragma unroll
                for (int i = 0; i < B_T; ++i) asm volatile("mbarrier.init.shared::cta.b64 [%0], %1;" :: "r"(bars + 8 * i), "r"(i == B_W ? 32 : 1) : "memory");
                expect_tx(bars + 8 * B_X, roleA ? 2560 : 1280);
                asm volatile("cp.async.bulk.shared::cluster.global.mbarrier::complete_tx::bytes [%0], [%1], 1280, [%2];"
                             :: "r"(sbase + OFF_XS), "l"(prm.x), "r"(bars + 8 * B_X) : "memory");
                if (roleA) {
                    asm volatile("cp.async.bulk.shared::cluster.global.mbarrier::complete_tx::bytes [%0], [%1], 1280, [%2];"
                                 :: "r"(sbase + OFF_XS + 1280), "l"(prm.gw), "r"(bars + 8 * B_X) : "memory");
                    expect_tx(bars + 8 * B_EX2, 4096);
                    expect_tx(bars + 8 * B_M, 128);
                }
                expect_tx(bars + 8 * B_EX0, roleA ? 4096 : 1024);
                expect_tx(bars + 8 * B_EX1, roleA ? 1024 : 512);
            } else {
#pragma unroll
                for (int i = 0; i < 12; ++i)
                    asm volatile("mbarrier.init.shared::cta.b64 [%0], %1;" :: "r"(tb + 8 * (k + 3 * i)), "r"(i < 2 && !roleA && k + 3 * i < 4 ? 128 : 1) : "memory");
            }
            asm volatile("fence.mbarrier_init.release.cluster;" ::: "memory");
        }
        __syncwarp();
        asm volatile("barrier.cluster.arrive.relaxed.aligned;" ::: "memory");
        asm volatile("setmaxnreg.dec.sync.aligned.u32 32;");
        if (k == 3) {
            uint32_t tag;
            asm volatile("ld.relaxed.gpu.global.u32 %0, [%1];" : "=r"(tag) : "l"(&prm.scr->epoch) : "memory");
            tag = (tag & 1u) ^ 1u;
            if (roleA) {
                u64* const mdst = &prm.scr->st[0][2 * lane][id][r];
#pragma unroll
                for (int i = 0; i < 4; ++i) st_pkt(mdst + (i & 1) * 64 + (i >> 1) * 4096, tag ^ 1u, 0u);
                sts32(sbase + OFF_POWN + 4096 + 4 * lane, 0x80000000u);
                mbar_wait(bars + 8 * B_X);
                float s = 0.f;
#pragma unroll 2
                for (int i = 0; i < 10; ++i) {
                    const uint32_t xw = lds32(sbase + OFF_XS + (lane + 32 * i) * 4), gv = lds32(sbase + OFF_XS + 1280 + (lane + 32 * i) * 4);
                    uint32_t pr;
                    asm("mul.rn.bf16x2 %0, %1, %2;" : "=r"(pr) : "r"(xw), "r"(gv));
                    s += bf_lo(pr) + bf_hi(pr);
                }
#pragma unroll
                for (int j = 16; j > 0; j >>= 1) s += shx(s, j);
                const float ga = bf_round(__fdividef(1.0f, 1.0f + __expf(-bf_round(s))));
                if (lane == 0) sts128(sbase + OFF_EX0, make_uint4(__float_as_uint(ga), __float_as_uint(bf_round(1.0f - ga)), 0xffff0000u, 0u));
                asm volatile("bar.arrive %0, 416;" :: "r"(BAR_Q) : "memory");
                bar_sync(BAR_Q + 1, 416);
                pin(lds32(sbase + OFF_EX0 + 12));
                const uint32_t ts = now_ns();
                st_pkt(mdst, tag, ts); st_pkt(mdst + 64, tag, ts);
                const uint32_t pdst = peer_addr(sbase + OFF_PIN, r ^ 1), pbar = peer_addr(bars + 8 * B_EX2, r ^ 1);
                bar_sync(BAR_HALF, 160);
                const int mo = (int)lds32(sbase + OFF_POWN + 4096 + 4 * lane);
                asm volatile("st.async.shared::cluster.mbarrier::complete_tx::bytes.b32 [%0], %1, [%2];"
                             :: "r"(pdst + 4096 + 4 * lane), "r"(mo), "r"(pbar + 8 * (B_M - B_EX2)) : "memory");
                bar_sync(BAR_ALL, NCOMP + 32);
                if (lane == 0)
                    asm volatile("cp.async.bulk.shared::cluster.shared::cta.mbarrier::complete_tx::bytes [%0], [%1], 4096, [%2];"
                                 :: "r"(pdst), "r"(sbase + OFF_POWN), "r"(pbar) : "memory");
                mbar_wait(bars + 8 * B_M);
                const int mi = (int)lds32(sbase + OFF_PIN + 4096 + 4 * lane);
                const float mm = __int_as_float(f2ord(max(mo, mi)));
                sts64(sbase + OFF_SMAX + 8 * lane, __float_as_uint(ex2(__int_as_float(f2ord(mo)) - mm)), __float_as_uint(ex2(__int_as_float(f2ord(mi)) - mm)));
                asm volatile("mbarrier.arrive.shared::cta.b64 _, [%0];" :: "r"(bars + 8 * B_W) : "memory");
                bar_sync(BAR_L, 160);
                const uint32_t la = sbase + OFF_LSUM + 4 * lane;
                const uint32_t lw = tag_word(__float_as_uint((ldsf(la) + ldsf(la + 128)) + (ldsf(la + 256) + ldsf(la + 384))), tag);
                st_pkt(mdst + 4096, lw, mo); st_pkt(mdst + 4160, lw, mo);
                TLT(19, 608);
            } else {
                const u64* ssrc = &prm.scr->st[0][me][lane][0];
                wait_until(t0, prm.ts);
                uint4 sv = poll_pkt2(ssrc, tag);
                const uint32_t last = t0 + __reduce_max_sync(0xffffffffu, max((int)(sv.y - t0), (int)(sv.w - t0)));
                if (lane == 0) {
                    sts32(sbase + OFF_LSUM, last);
                    asm volatile("mbarrier.arrive.shared::cta.b64 _, [%0];" :: "r"(bars + 8 * B_EX2) : "memory");
                }
                while ((int)(now_ns() - last) < prm.ls) { }
                sv = poll_pkt2(ssrc + 4096, tag);
                const uint2 s0 = make_uint2(sv.x, sv.y), s1 = make_uint2(sv.z, sv.w);
                const float mg = __int_as_float(f2ord(__reduce_max_sync(0xffffffffu, max((int)s0.y, (int)s1.y))));
                const float e0 = ex2(__int_as_float(f2ord((int)s0.y)) - mg), e1 = ex2(__int_as_float(f2ord((int)s1.y)) - mg);
                const float e = fmaxf(e0, e1);
                float lg = e0 * F(s0.x & ~1u) + e1 * F(s1.x & ~1u);
#pragma unroll
                for (int j = 16; j > 0; j >>= 1) lg += shx(lg, j);
                sts32(sbase + OFF_SMAX + 4 * lane, __float_as_uint(__fdividef(e, lg)));
                asm volatile("mbarrier.arrive.shared::cta.b64 _, [%0];" :: "r"(bars + 8 * B_W) : "memory");
                TLT(19, 608);
            }
            return;
        }
        const int total = roleA ? (me >= 24 ? A_END : A_W2) : P_END;
        const int ph = (me * prm.ph) >> 6;
#define MONITOR()
#pragma unroll 1
        for (int i = roleA ? k : (k ? k + 3 : 6); i < total; i += 3) {
            if (roleA && !ffn && i >= A_W1 && i < A_W2) continue;
            const uint4 e = prm.tile[roleA][i];
            const uint32_t c0 = (int)(short)e.z + (e.w & 255u) * id + ((e.w >> 8) & 255u) * r;
            const uint32_t c1 = (e.z >> 16) + 32 * (((e.w >> 16) & 255u) * id + ((int)e.w >> 24) * r);
            if (!roleA && i >= CAP) mbar_wait(tb + 8 * (i - CAP));
            if (!roleA && i >= P_WO && i < P_WO + 3) {
                asm volatile("barrier.cluster.wait.aligned;" ::: "memory");
                mbar_wait(bars + 8 * B_EX0);
            }
            if (lane == 0) expect_tx(tb + 8 * i, (e.x >> 24) << 10);
            const int when = min((int)e.y + ph, prm.tend);
            while ((int)(now_ns() - t0) < when) { MONITOR(); }
            if (lane == 0) {
                tma3d(sbase + (e.x & 0xfffffu), mapbase + 128 * ((e.x >> 20) & 7u), c1, c0, tb + 8 * i);
            }
            __syncwarp();
        }
        return;
    }

    asm volatile("setmaxnreg.inc.sync.aligned.u32 112;");
    Scratch* const scr = prm.scr;
    uint32_t epoch;
    asm volatile("ld.relaxed.gpu.global.u32 %0, [%1];" : "=r"(epoch) : "l"(&scr->epoch) : "memory");
    asm volatile("barrier.cluster.arrive.relaxed.aligned;" ::: "memory");
    asm volatile("barrier.cluster.wait.aligned;" ::: "memory");
    if (!roleA) asm volatile("cp.async.mbarrier.arrive.noinc.shared::cta.b64 [%0];" :: "r"(tb + 8 * (warp >> 2)) : "memory");
    const uint32_t tag = (epoch & 1u) ^ 1u;
    const int g = lane >> 2, tq = lane & 3;
    const uint32_t tsw = sbase + ((lane & 7) + (lane >> 4) * 8) * 128 + (((2 * (warp & 3) + ((lane >> 3) & 1)) ^ (lane & 7)) << 4);
    float d[16];
    const bool reducer = roleA && me >= 24;
    uint32_t* const odst = &scr->x4[warp + 16 * (tq >> 1)][me][g + 8 * (tq & 1)];
    {
        const uint4 em = make_uint4(tag ^ 1u, 0u, tag ^ 1u, 0u);
        if (roleA) {
            if (ffn && warp == 0) st_word(&scr->xh[32 * me + lane], tag ^ 1u);
            if (prm.prew) {
                wait_until(t0, prm.prew + 40 * warp);
                u64* const xd = &scr->x2[2 * ((t & 127) >> 3) + r][id][16 * (warp >> 2) + 2 * (lane & 7)];
                st_pkt2(xd, em); st_pkt2(xd + 32 * 32 * 64, em);
            }
        } else {
            if ((lane & 14) == 0) st_pkt(&scr->x1[me][4 * warp + 2 * tq + (lane >> 4)], tag ^ 1u, 0u);
            st_word(odst, tag ^ 1u);
            if (tq < 2 && warp < 8) st_word(odst + 32 * 64 * 16, tag ^ 1u);
        }
    }
    mbar_wait(bars + 8 * B_X);

    if (roleA) {
        uint32_t fa[64];
        const int wg = warp >> 2;
        const uint32_t pb = tb + 8 * (A_C + 2 * (~wg & 2));
#define PRELOAD() do { if (wg != 1) { mbar_wait2(pb, pb + 8); mbar_wait2(pb + 16, pb + 24); } \
        _Pragma("unroll") for (int ks = 0; ks < 8; ++ks) \
            ldsm4t(fa + 4 * ks, tsw + OFF_C + (wg >> 1) * 32768 + (wg & 1) * 4096 + (ks >> 1) * 8192 + (ks & 1) * 2048); } while (0)
        const int h0 = 4 * (warp - 8);
        const int hq = h0 + (lane >> 3);
        const u64* src = &scr->x1[2 * hq + r][2 * (lane & 7)];
        const uint32_t qa = sbase + OFF_Q + hq * 128 + (((lane ^ hq) & 7) << 4);
        uint4 v[4];
        if (warp < 8) {
            const uint32_t base = sbase + OFF_C + (warp >> 1) * 8192 + (16 * (warp & 1) + (lane & 7) + ((lane >> 3) & 1) * 8) * 128;
            const u64 qd = sdesc(sbase + OFF_Q);
            const uint32_t rdst = peer_addr(sbase + OFF_SREM + t * 16, r ^ 1), rbar = peer_addr(bars + 8 * B_EX0, r ^ 1);
            pin(rdst); pin(rbar);
            zero16(d);
#pragma unroll
            for (int cp = 1; cp >= 0; --cp) {
                mbar_wait(tb + 8 * (A_C + 4 * (1 - cp) + (warp >> 1)));
#pragma unroll
                for (int k = 0; k < 8; ++k) ldsm4(fa + 32 * cp + 4 * k, base + cp * 32768 + (k >> 2) * 4096 + (((2 * (k & 3) + (lane >> 4)) ^ (lane & 7)) << 4));
            }
            if (wg) { mbar_wait2(pb, pb + 8); mbar_wait2(pb + 16, pb + 24); }
            TLT(1, 224);
            bar_sync(BAR_Q + wg, 416);
            if (wg) spin(prm.skew);
            TLT(2, 0);
            asm volatile("wgmma.fence.sync.aligned;" ::: "memory");
#pragma unroll
            for (int ks = 0; ks < 16; ++ks) wgmma_rs(d, fa + 4 * ks, qd + (ks >> 2) * 256 + (ks & 3) * 2);
            asm volatile("wgmma.commit_group.sync.aligned;" ::: "memory");
            asm volatile("wgmma.wait_group.sync.aligned 0;" ::: "memory");
            if (wg == 0) {
#pragma unroll
                for (int i = 0; i < 2; ++i)
                    asm volatile("st.async.shared::cluster.mbarrier::complete_tx::bytes.v4.b32 [%0], {%1,%2,%3,%4}, [%5];"
                                 :: "r"(rdst + i * 2048), "r"(pack_bf(d[8 * i], d[8 * i + 1])), "r"(pack_bf(d[8 * i + 2], d[8 * i + 3])),
                                    "r"(pack_bf(d[8 * i + 4], d[8 * i + 5])), "r"(pack_bf(d[8 * i + 6], d[8 * i + 7])), "r"(rbar) : "memory");
            }
            TLT(3, 0);
            TLT(17, 128);
        } else {
            pin(src); pin(qa);
            wait_until(t0, prm.tq0);
#pragma unroll
            for (int k = 0; k < 3; ++k) v[k] = ld_pkt2(src + 16 * k);
            while ((int)(now_ns() - t0) < prm.tq) { }
            TLT(8, 256);
            v[3] = ld_pkt2(src + 48);
        }
        PRELOAD();
        if (warp >= 8) {
#pragma unroll 1
            for (int it = 0; it < SPIN_MAX; ++it) {
                if (__all_sync(0xffffffffu, fresh2(v[0], tag) && fresh2(v[1], tag) && fresh2(v[2], tag) && fresh2(v[3], tag))) break;
#pragma unroll
                for (int k = 0; k < 4; ++k) if (!fresh2(v[k], tag)) v[k] = ld_pkt2(src + 16 * k);
                TLT(20, 256);
            }
#pragma unroll
            for (int k = 0; k < 4; ++k) {
                v[k].x &= ~1u; v[k].z &= ~1u;
                sts128(qa + k * 4096, v[k]);
            }
            asm volatile("fence.proxy.async.shared::cta;" ::: "memory");
            asm volatile("bar.arrive %0, 416;" :: "r"(BAR_Q) : "memory");
            asm volatile("bar.arrive %0, 416;" :: "r"(BAR_Q + 1) : "memory");
            TLT(9, 256);
        }
        const bool b4 = lane & 16, b3 = lane & 8, b2 = lane & 4;
        const int myhead = 8 * (g >> 1) + 2 * tq + (g & 1);
        const u64 pd = sdesc(sbase + OFF_PIN);
        const uint32_t oa = sbase + OFF_OT + ((lane & 7) + (lane >> 4) * 8) * 528 + warp * 32 + ((lane >> 3) & 1) * 16;
        const int hh = (t & 127) >> 3;
        const uint32_t ob = sbase + OFF_OT + hh * 528 + wg * 128 + (lane & 7) * 16;
        u64* const xdst = &scr->x2[2 * hh + r][id][16 * wg + 2 * (lane & 7)];
        float d2[16];
        if (wg == 1) {
            float u[8];
            uint32_t pk[8];
            mbar_wait(bars + 8 * B_EX0);
            TLT(18, 128);
#pragma unroll
            for (int i = 0; i < 2; ++i) {
                const uint4 o = lds128(sbase + OFF_SREM + (t & 127) * 16 + i * 2048);
                d[8 * i] += bf_lo(o.x); d[8 * i + 1] += bf_hi(o.x); d[8 * i + 2] += bf_lo(o.y); d[8 * i + 3] += bf_hi(o.y);
                d[8 * i + 4] += bf_lo(o.z); d[8 * i + 5] += bf_hi(o.z); d[8 * i + 6] += bf_lo(o.w); d[8 * i + 7] += bf_hi(o.w);
            }
#pragma unroll
            for (int i = 0; i < 8; ++i) u[i] = fmaxf(d[4 * (i >> 1) + (i & 1)], d[4 * (i >> 1) + (i & 1) + 2]);
#pragma unroll
            for (int i = 0; i < 4; ++i) u[i] = fmaxf(b4 ? u[i + 4] : u[i], shx(b4 ? u[i] : u[i + 4], 16));
#pragma unroll
            for (int i = 0; i < 2; ++i) u[i] = fmaxf(b3 ? u[i + 2] : u[i], shx(b3 ? u[i] : u[i + 2], 8));
            asm volatile("red.shared.max.s32 [%0], %1;" :: "r"(sbase + OFF_POWN + 4096 + 4 * myhead),
                         "r"(f2ord(__float_as_int(fmaxf(b2 ? u[1] : u[0], shx(b2 ? u[0] : u[1], 4))))) : "memory");
            bar_sync(BAR_HALF, 160);
            TLT(13, 128);
#pragma unroll
            for (int j = 0; j < 4; ++j) {
                const uint2 mi = lds64(sbase + OFF_POWN + 4096 + 32 * j + 8 * tq);
                const float m0 = __int_as_float(f2ord((int)mi.x)), m1 = __int_as_float(f2ord((int)mi.y));
                pk[2 * j] = pack_bf(ex2(d[4 * j] - m0), ex2(d[4 * j + 1] - m1));
                pk[2 * j + 1] = pack_bf(ex2(d[4 * j + 2] - m0), ex2(d[4 * j + 3] - m1));
            }
            stsm4t(tsw + OFF_POWN, pk);
            stsm4t(tsw + OFF_POWN + 2048, pk + 4);
            asm volatile("fence.proxy.async.shared::cta;" ::: "memory");
            asm volatile("bar.arrive %0, 544;" :: "r"(BAR_ALL) : "memory");
            const uint32_t hm = lds32(sbase + OFF_EX0 + 8);
#pragma unroll
            for (int j = 0; j < 4; ++j) {
                u[2 * j] = F((pk[2 * j] << 16) & hm) + bf_lo(pk[2 * j + 1]);
                u[2 * j + 1] = F(pk[2 * j] & hm) + bf_hi(pk[2 * j + 1]);
            }
#pragma unroll
            for (int i = 0; i < 4; ++i) u[i] = (b4 ? u[i + 4] : u[i]) + shx(b4 ? u[i] : u[i + 4], 16);
#pragma unroll
            for (int i = 0; i < 2; ++i) u[i] = (b3 ? u[i + 2] : u[i]) + shx(b3 ? u[i] : u[i + 2], 8);
            sts32(sbase + OFF_LSUM + ((warp & 3) * 32 + myhead) * 4, __float_as_uint((b2 ? u[1] : u[0]) + shx(b2 ? u[0] : u[1], 4)));
            zero16(d); zero16(d2);
            asm volatile("bar.arrive %0, 160;" :: "r"(BAR_L) : "memory");
            bar_sync(BAR_WG + 1, 128);
        } else {
            pin(oa); pin(ob); pin(xdst);
            zero16(d); zero16(d2);
            bar_sync(BAR_ALL, NCOMP + 32);
        }
        TLT(5, 256);
        asm volatile("wgmma.fence.sync.aligned;" ::: "memory");
#pragma unroll
        for (int ks = 0; ks < 4; ++ks) wgmma_rs(d, fa + 16 + 4 * ks, pd + 320 + ks * 2);
        mbar_wait2(bars + 8 * B_EX2, bars + 8 * B_W);
        TLT(4, 256);
#pragma unroll
        for (int ks = 0; ks < 4; ++ks) wgmma_rs(d2, fa + 4 * ks, pd + ks * 2);
        asm volatile("wgmma.commit_group.sync.aligned;" ::: "memory");
        uint4 ab[4];
#pragma unroll
        for (int j = 0; j < 4; ++j) ab[j] = lds128(sbase + OFF_SMAX + 64 * j + 16 * tq);
        asm volatile("wgmma.wait_group.sync.aligned 0;" ::: "memory");
        {
            uint32_t ok[8];
#pragma unroll
            for (int i = 0; i < 8; ++i)
                ok[i] = pack_bf(F(ab[i >> 1].x) * d[2 * i] + F(ab[i >> 1].y) * d2[2 * i], F(ab[i >> 1].z) * d[2 * i + 1] + F(ab[i >> 1].w) * d2[2 * i + 1]);
            stsm4t(oa, ok);
            stsm4t(oa + 16 * 528, ok + 4);
            bar_sync(BAR_WG + wg, 128);
            TLT(14, 128);
#pragma unroll
            for (int i = 0; i < 2; ++i) {
                uint4 v = lds128(ob + i * 16 * 528);
                v.x = tag_word(v.x, tag); v.z = tag_word(v.z, tag);
                st_pkt2(xdst + i * (32 * 32 * 64), v);
            }
        }
        TLT(6, 128);
        if (ffn) {
            uint32_t a[20], b[12];
            const uint32_t xa = sbase + OFF_XS + 640 * r + wg * 160 + (lane >> 3) * 16;
            ldsm4(b, xa); ldsm4(b + 4, xa + 64); ldsm4(b + 8, xa + 128 - (lane & 16) * 2);
            mbar_wait2(tb + 8 * (A_W1 + (5 * wg >> 2)), tb + 8 * (A_W1 + wg + 1));
#pragma unroll
            for (int k = 0; k < 5; ++k) ldsm4t(a + 4 * k, tsw + OFF_W1 + (5 * wg + k) * 2048);
            zero16(d);
#pragma unroll
            for (int k = 0; k < 5; ++k) mma_w(d + 4 * (k & 3), a + 4 * k, b[2 * k], b[2 * k + 1]);
            const uint32_t rank = (warp >> 1) & 1;
            if (tq < 2)
                st_async1(peer_addr(sbase + OFF_EX1 + ((4 * r + wg) * 32 + 16 * (warp & 1) + g + 8 * tq) * 4, rank),
                          tq ? (d[2] + d[6]) + (d[10] + d[14]) : (d[0] + d[4]) + (d[8] + d[12]), peer_addr(bars + 8 * B_EX1, rank));
            if (warp == 0) {
                mbar_wait(bars + 8 * B_EX1);
                const uint32_t ep = sbase + OFF_EX1 + lane * 4;
                const float h = bf_round(((ldsf(ep) + ldsf(ep + 128)) + (ldsf(ep + 256) + ldsf(ep + 384))) +
                                         ((ldsf(ep + 512) + ldsf(ep + 640)) + (ldsf(ep + 768) + ldsf(ep + 896))));
                st_word(&scr->xh[32 * me + lane], __float_as_uint(bf_round(__fdividef(h, 1.0f + __expf(-h)))) | tag);
            }
        }
        TLT(7, 0);
    } else if (warp < 8) {
        uint32_t xa = sbase + OFF_XS + 640 * r + (lane >> 3) * 16;
        uint32_t wa = tsw + OFF_WO + (warp >> 2) * 4096;
        const uint32_t rdst = peer_addr(sbase + OFF_EX0 + (r * 128 + 16 * warp + g + 8 * (tq & 1)) * 4, tq >> 1);
        const uint32_t rbar = peer_addr(bars + 8 * B_EX0, tq >> 1);
        pin(rdst); pin(rbar);
        zero16(d);
#pragma unroll 1
        for (int kb = 0; kb < 10; ++kb) {
            uint32_t b[4], a[8];
            ldsm4(b, xa);
            mbar_wait(tb + 8 * (P_WQ + kb));
            ldsm4t(a, wa); ldsm4t(a + 4, wa + 2048);
            mma_w(d, a, b[0], b[1]); mma_w(d + 4, a + 4, b[2], b[3]);
            xa += 64; wa += 8192;
        }
        st_async1(rdst, (tq & 1) ? d[2] + d[6] : d[0] + d[4], rbar);
    }

    if (!roleA) {
        TLT(1, 0);
        {
            const uint32_t base = sbase + OFF_WUK + (warp >> 1) * 8192 + ((warp & 1) * 16 + (lane & 7) + ((lane >> 3) & 1) * 8) * 128;
            u64* const qdst = &scr->x1[me][4 * warp + 2 * tq + (lane >> 4)];
            pin(base); pin(qdst);
            mbar_wait(bars + 8 * B_EX0);
            const uint4 q0 = lds128(sbase + OFF_EX0 + lane * 16), q1 = lds128(sbase + OFF_EX0 + 512 + lane * 16);
            const uint32_t w0 = pack_bf(F(q0.x) + F(q1.x), F(q0.y) + F(q1.y)), w1 = pack_bf(F(q0.z) + F(q1.z), F(q0.w) + F(q1.w));
            sts64(sbase + OFF_O + lane * 8, w0, w1);
            __syncwarp();
            uint32_t b[16];
#pragma unroll
            for (int k = 0; k < 4; ++k) ldsm4(b + 4 * k, sbase + OFF_O + (lane >> 3) * 16 + 64 * k);
            TLT(2, 0);
            zero16(d);
            mbar_wait(tb + 8 * (P_WUK + (warp >> 1)));
            uint32_t a[32];
#pragma unroll
            for (int k = 0; k < 8; ++k) ldsm4(a + 4 * k, base + (k >> 2) * 4096 + (((2 * (k & 3) + (lane >> 4)) ^ (lane & 7)) << 4));
#pragma unroll
            for (int k = 0; k < 8; ++k) mma_w(d + 4 * (k & 3), a + 4 * k, b[2 * k], b[2 * k + 1]);
            const float sc = 0.08838834764831845f * 1.4426950408889634f;
            const float v = ((tq & 1) ? (d[2] + d[6]) + (d[10] + d[14]) : (d[0] + d[4]) + (d[8] + d[12])) * sc;
            const uint32_t w = pack_bf(v, __shfl_down_sync(0xffffffffu, v, 4));
            const uint32_t w2 = __shfl_down_sync(0xffffffffu, w, 8);
            if ((lane & 14) == 0) st_pkt(qdst, tag_word(w, tag), w2);
        }
        TLT(3, 480);
        {
            uint32_t a[32];
            const int a0 = 4 * (warp >> 1);
            const u64* src = &scr->x2[me][a0][32 * (warp & 1) + lane];
            const uint32_t rank = (warp >> 2) & 1;
            const uint32_t rdst = peer_addr(sbase + OFF_EX1 + (2 * r + (warp >> 3)) * 144 + (16 * (warp & 3) + g + 8 * (tq & 1)) * 2, rank);
            const uint32_t rbar = peer_addr(bars + 8 * B_EX1, rank);
            const uint32_t ow = sbase + OFF_O + (warp >> 1) * 528 + (warp & 1) * 256 + lane * 8;
            const uint32_t ol = sbase + OFF_O + (lane & 7) * 528 + (warp >> 3) * 256 + (lane >> 3) * 16;
            const uint32_t wm = tsw + OFF_WO + (warp >> 3) * 16384 + rank * 4096, ob_ = tb + 8 * (P_WO + 2 * (warp >> 3));
            const uint32_t cl = sbase + OFF_EX1 + (lane & 3) * 144 + (lane >> 3) * 16;
            pin(src); pin(rdst); pin(rbar); pin(ow); pin(ol); pin(wm); pin(cl); pin(odst);
            const uint32_t ub = tb + 8 * (P_WUV + 4 * (warp >> 3));
            mbar_wait2(ub, ub + 8); mbar_wait2(ub + 16, ub + 24);
#pragma unroll
            for (int k = 0; k < 8; ++k) ldsm4t(a + 4 * k, tsw + OFF_WUV + (warp >> 3) * 32768 + rank * 4096 + (k >> 1) * 8192 + (k & 1) * 2048);
            zero16(d);
            mbar_wait(bars + 8 * B_EX2);
            TLT(4, 0);
            const uint32_t last = lds32(sbase + OFF_LSUM);
            while ((int)(now_ns() - last) < prm.lb) { }
            TLT(14, 0);
            uint2 v[4];
#pragma unroll
            for (int i = 0; i < 4; ++i) v[i] = ld_pkt(src + 64 * i);
            uint32_t w0[16], early;
            asm volatile("{.reg .pred p, q; mbarrier.test_wait.parity.shared::cta.b64 p, [%1], 0; mbarrier.test_wait.parity.shared::cta.b64 q, [%1+8], 0;"
                         " and.pred p, p, q; selp.u32 %0, 1, 0, p;}" : "=r"(early) : "r"(ob_) : "memory");
            early = __all_sync(0xffffffffu, early);
#define LOAD_WO(dst_, i_) do { _Pragma("unroll") for (int k = 0; k < 4; ++k) ldsm4t((dst_) + 4 * k, wm + (i_) * 32768 + (k >> 1) * 8192 + (k & 1) * 2048); } while (0)
            if (early) LOAD_WO(w0, 0);
            mbar_wait(bars + 8 * B_W);
            const uint4 wq4 = lds128(sbase + OFF_SMAX + 4 * a0);
            const float wn[4] = {F(wq4.x), F(wq4.y), F(wq4.z), F(wq4.w)};
#pragma unroll 1
            for (int it = 0; it < SPIN_MAX; ++it) {
                if (__all_sync(0xffffffffu, (((v[0].x ^ tag) | (v[1].x ^ tag) | (v[2].x ^ tag) | (v[3].x ^ tag)) & 1u) == 0)) break;
#pragma unroll
                for (int i = 0; i < 4; ++i) if ((v[i].x ^ tag) & 1u) v[i] = ld_pkt(src + 64 * i);
                TLT(20, 0);
            }
            TLT(5, 0);
            float c[4] = {0.f, 0.f, 0.f, 0.f};
#pragma unroll
            for (int i = 0; i < 4; ++i) {
                c[0] = fmaf(wn[i], bf_lo(v[i].x & ~1u), c[0]); c[1] = fmaf(wn[i], bf_hi(v[i].x), c[1]);
                c[2] = fmaf(wn[i], bf_lo(v[i].y), c[2]); c[3] = fmaf(wn[i], bf_hi(v[i].y), c[3]);
            }
            sts64(ow, pack_bf(c[0], c[1]), pack_bf(c[2], c[3]));
            bar_sync(BAR_ALL, NCOMP);
            TLT(6, 0);
            uint32_t b[16];
#pragma unroll
            for (int k = 0; k < 4; ++k) ldsm4(b + 4 * k, ol + 64 * k);
#pragma unroll
            for (int k = 0; k < 8; ++k) mma_w(d + 4 * (k & 3), a + 4 * k, b[2 * k], b[2 * k + 1]);
            const float c0 = ((d[0] + d[1]) + (d[4] + d[5])) + ((d[8] + d[9]) + (d[12] + d[13]));
            const float c1 = ((d[2] + d[3]) + (d[6] + d[7])) + ((d[10] + d[11]) + (d[14] + d[15]));
            float v_ = ((tq & 1) ? c1 : c0) + shx((tq & 1) ? c0 : c1, 1);
            v_ += shx(v_, 2);
            const float vn = __shfl_down_sync(0xffffffffu, v_, 4);
            if ((lane & 6) == 0)
                asm volatile("st.async.shared::cluster.mbarrier::complete_tx::bytes.b32 [%0], %1, [%2];" :: "r"(rdst), "r"(pack_bf(v_, vn)), "r"(rbar) : "memory");
            TLT(15, 0);
            if (!early) { mbar_wait2(ob_, ob_ + 8); LOAD_WO(w0, 0); }
            mbar_wait2(ob_ + 32, ob_ + 40);
            LOAD_WO(a, 1);
            uint32_t late = 0;
            if (warp < 8) {
                asm volatile("{.reg .pred p, q; mbarrier.test_wait.parity.shared::cta.b64 p, [%1], 0; mbarrier.test_wait.parity.shared::cta.b64 q, [%1+8], 0;"
                             " and.pred p, p, q; selp.u32 %0, 0, 1, p;}" : "=r"(late) : "r"(ob_ + 64) : "memory");
                late = __any_sync(0xffffffffu, late);
                if (!late) LOAD_WO(a + 16, 2);
            }
            zero16(d);
            mbar_wait(bars + 8 * B_EX1);
            TLT(7, 0);
            ldsm4(b, cl); ldsm4(b + 4, cl + 64);
#pragma unroll
            for (int k = 0; k < 4; ++k) {
                mma_w(d + 4 * (k & 1), w0 + 4 * k, b[2 * k], b[2 * k + 1]);
                mma_w(d + 8 + 4 * (k & 1), a + 4 * k, b[2 * k], b[2 * k + 1]);
            }
            {
                const float lo = tq < 2 ? (d[0] + d[1]) + (d[4] + d[5]) : (d[8] + d[9]) + (d[12] + d[13]);
                const float hi = tq < 2 ? (d[2] + d[3]) + (d[6] + d[7]) : (d[10] + d[11]) + (d[14] + d[15]);
                st_word(odst, tag_word(__float_as_uint(((tq & 1) ? hi : lo) + shx((tq & 1) ? lo : hi, 1)), tag));
            }
            if (warp < 8) {
                if (late) { mbar_wait2(ob_ + 64, ob_ + 72); LOAD_WO(a + 16, 2); }
                zero16(d);
#pragma unroll
                for (int k = 0; k < 4; ++k) mma_w(d + 4 * k, a + 16 + 4 * k, b[2 * k], b[2 * k + 1]);
                const float lo = ((d[0] + d[1]) + (d[4] + d[5])) + ((d[8] + d[9]) + (d[12] + d[13]));
                const float hi = ((d[2] + d[3]) + (d[6] + d[7])) + ((d[10] + d[11]) + (d[14] + d[15]));
                const float o = ((tq & 1) ? hi : lo) + shx((tq & 1) ? lo : hi, 1);
                if (tq < 2) st_word(odst + 32 * 64 * 16, tag_word(__float_as_uint(o), tag));
            }
        }
    }
    TLT(10, 0);
    if (reducer) {
        const uint32_t rp = sbase + OFF_O + ((lane >> 4) * 128 + (lane & 15)) * 4;
        __nv_bfloat16* const op = prm.out + 16 * (me - 24) + (lane & 15);
        const float gg = ldsf(sbase + OFF_EX0 + (warp >> 3) * 4);
        pin(rp); pin(op);
        if (warp < 8) {
            const uint32_t* rsrc = &scr->x4[me - 24][8 * warp][4 * lane];
            const uint32_t rw = sbase + OFF_O + (warp * 16 + 4 * tq + ((lane >> 3) & 2) + ((lane >> 3) & 1)) * 4;
            pin(rw);
            wait_until(t0, prm.tr);
            uint4 rv = ld_word4(rsrc);
#pragma unroll 1
            for (int it = 0; it < SPIN_MAX; ++it) {
                const bool ok = fresh4(rv, tag);
                if (__all_sync(0xffffffffu, ok)) break;
                if (!ok) rv = ld_word4(rsrc);
            }
            const bool b4 = lane & 16, b3 = lane & 8;
            const float o0 = F(rv.x & ~1u), o1 = F(rv.y & ~1u), o2 = F(rv.z & ~1u), o3 = F(rv.w & ~1u);
            const float y0 = (b4 ? o2 : o0) + shx(b4 ? o0 : o2, 16), y1 = (b4 ? o3 : o1) + shx(b4 ? o1 : o3, 16);
            float y = (b3 ? y1 : y0) + shx(b3 ? y0 : y1, 8);
            y += shx(y, 4);
            if (!(lane & 4)) sts32(rw, __float_as_uint(gg * y));
        } else {
            const int w8 = warp - 8, nt = w8 < 6 ? 7 : 6;
            const uint32_t hs = sbase + OFF_Q + w8 * 512;
            const uint32_t* hsrc = &scr->xh[256 * (lane >> 3) + 32 * w8 + 4 * (lane & 7)];
            const uint32_t wa = sbase + OFF_W2 + (32 * w8 + (lane & 7) + (lane >> 4) * 8) * 32 + ((lane >> 3) & 1) * 16;
            const uint32_t rw = sbase + OFF_O + (warp * 16 + g + 8 * tq) * 4;
            pin(wa); pin(rw);
            wait_until(t0, prm.tr1);
            uint4 h0 = ld_word4(hsrc), h1 = make_uint4(tag, tag, tag, tag);
            if (4 + (lane >> 3) < nt) h1 = ld_word4(hsrc + 1024);
#pragma unroll 1
            for (int it = 0; it < SPIN_MAX; ++it) {
                const bool k0 = fresh4(h0, tag), k1 = fresh4(h1, tag);
                if (__all_sync(0xffffffffu, k0 && k1)) break;
                __nanosleep(60);
                if (!k0) h0 = ld_word4(hsrc);
                if (!k1) h1 = ld_word4(hsrc + 1024);
            }
            sts64(hs + lane * 8, __byte_perm(h0.x, h0.y, 0x7632), __byte_perm(h0.z, h0.w, 0x7632));
            sts64(hs + 256 + lane * 8, __byte_perm(h1.x, h1.y, 0x7632), __byte_perm(h1.z, h1.w, 0x7632));
            __syncwarp();
            uint32_t b[28];
#pragma unroll
            for (int j = 0; j < 7; ++j) ldsm4(b + 4 * j, hs + j * 64 + (lane >> 3) * 16);
            TLT(12, 256);
            zero16(d);
#pragma unroll
            for (int jj = 0; jj < 4; ++jj) {
                uint32_t a[16];
                if (jj < 3) mbar_wait2(tb + 8 * (A_W2 + 2 * jj), tb + 8 * (A_W2 + 2 * jj + 1)); else mbar_wait(tb + 8 * (A_W2 + 6));
#pragma unroll
                for (int k = 0; k < (jj < 3 ? 4 : 2); ++k) ldsm4t(a + 4 * k, wa + (2 * jj + (k >> 1)) * 8192 + (k & 1) * 512);
#pragma unroll
                for (int k = 0; k < (jj < 3 ? 4 : 2); ++k) mma_w(d + 4 * k, a + 4 * k, b[8 * jj + 2 * k], b[8 * jj + 2 * k + 1]);
            }
            if (tq < 2) sts32(rw, __float_as_uint(gg * (tq ? (d[2] + d[6]) + (d[10] + d[14]) : (d[0] + d[4]) + (d[8] + d[12]))));
            TLT(16, 256);
        }
        if (warp != 15) asm volatile("bar.arrive %0, 512;" :: "r"(BAR_Q) : "memory");
        else {
            bar_sync(BAR_Q, NCOMP);
            float z = ((ldsf(rp) + ldsf(rp + 64)) + (ldsf(rp + 128) + ldsf(rp + 192))) + ((ldsf(rp + 256) + ldsf(rp + 320)) + (ldsf(rp + 384) + ldsf(rp + 448)));
            z += shx(z, 16);
            if (lane < 16) *op = __float2bfloat16_rn(z);
            if (me == 24 && lane == 0) asm volatile("st.relaxed.gpu.global.u32 [%0], %1;" :: "l"(&scr->epoch), "r"(epoch + 1u) : "memory");
            TLT(11, 480);
        }
    }
}

typedef CUresult (*EncodeFn)(CUtensorMap*, CUtensorMapDataType, cuuint32_t, void*, const cuuint64_t*, const cuuint64_t*,
                             const cuuint32_t*, const cuuint32_t*, CUtensorMapInterleave, CUtensorMapSwizzle,
                             CUtensorMapL2promotion, CUtensorMapFloatOOBfill);

void make_map(EncodeFn enc, CUtensorMap* m, void* base, uint64_t cols, uint64_t rows, uint32_t brows, uint32_t bblk, uint32_t bw = 64) {
    cuuint64_t dims[3] = {bw, rows, cols / bw};
    cuuint64_t strides[2] = {cols * 2, bw * 2};
    cuuint32_t box[3] = {bw, brows, bblk};
    cuuint32_t es[3] = {1, 1, 1};
    enc(m, CU_TENSOR_MAP_DATA_TYPE_BFLOAT16, 3, base, dims, strides, box, es, CU_TENSOR_MAP_INTERLEAVE_NONE,
        bw == 64 ? CU_TENSOR_MAP_SWIZZLE_128B : CU_TENSOR_MAP_SWIZZLE_NONE, CU_TENSOR_MAP_L2_PROMOTION_NONE, CU_TENSOR_MAP_FLOAT_OOB_FILL_NONE);
}

}

extern "C" void kernel_launch(void* const* d_in, const int* in_sizes, int n_in, void* d_out, int out_size) {
    (void)in_sizes; (void)n_in; (void)out_size;
    static EncodeFn enc = nullptr;
    static void* scr = nullptr;
    if (!enc) {
        cudaFuncSetAttribute(fused_kernel, cudaFuncAttributeMaxDynamicSharedMemorySize, SMEM_BYTES);
        cudaGetSymbolAddress(&scr, g_scr);
        void* fn = nullptr;
        cudaDriverEntryPointQueryResult qr;
        cudaGetDriverEntryPoint("cuTensorMapEncodeTiled", &fn, cudaEnableDefault, &qr);
        enc = (EncodeFn)fn;
    }
    Params prm;
    prm.x = (const __nv_bfloat16*)d_in[0];
    prm.gw = (const __nv_bfloat16*)d_in[9];
    prm.out = (__nv_bfloat16*)d_out;
    prm.scr = (Scratch*)scr;
    const Tune tn = tune();
    prm.tq0 = tn.TQ0; prm.tq = tn.TQ; prm.ts = tn.TS; prm.lb = tn.LB; prm.ls = tn.LS; prm.skew = TV(SKEW, 120); prm.tr = TV(TR, 9350); prm.tr1 = TV(TR1, 8400); prm.prew = TV(PW, 3300); prm.tend = TV(TEND, 20000); prm.ph = tn.PH;
    for (int i = 0; i < 36; ++i) {
        auto mk = [&](int dst, int map, int kb, int when, int blk, int row, int blki, int blkr, int rowi, int rowr) {
            if (map == 2 || map == 3 || map >= 5) {
                const int v = when - tn.T3, a = v < tn.V1 ? v : tn.V1, c = v > tn.V2 ? v - tn.V2 : 0, b = v - a - c;
                when = tn.T3 + (a * tn.S1 + b * tn.S2 + c * tn.S3) / 100;
                if (map < 4 && when > TV(PP0, 100000)) when += TV(PPL, 0);
                if (map == 6) when = i - A_W2 < TV(NE, 0) ? TV(TE, 5800) + (i - A_W2) * TV(DE, 200) : TV(TW2, 7700) + (i - A_W2 - TV(NE, 0)) * TV(DW2, 90);
            }
            if ((TV(NOLOAD, 0) >> map) & 1) kb = 0;
            return make_uint4(dst | map << 20 | kb << 24, when, (blk & 0xffff) | row << 16, blki | blkr << 8 | rowi / 32 << 16 | (unsigned)(rowr / 32) << 24);
        };
        const int j = i - P_WO, f = i - A_W2;
        prm.tile[0][i] = i < P_WUK ? mk(OFF_WO + i * 8192, 0, 8, tn.TP1 + (i - 17) * tn.DD1, 0, 32 * i, 2, 0, 0, 320)
                       : i < P_WUV ? mk((i - P_WUK) * 8192, 1, 8, tn.TP1 + (i - 17) * tn.DD1, 0, 32 * (i - P_WUK), 2, 0, 0, 256)
                       : i < P_WO  ? mk((i - P_WUK) * 8192, 2, 8, tn.T3 + (i - P_WUV) * tn.DP2, 0, 32 * (i - P_WUV), 2, 0, 0, 256)
                                   : mk(OFF_WO + j * 8192, 3, 8, tn.T3 + 8 * tn.DP2 + j * tn.DP3, j & ~1, 32 * (j & 1), 0, 0, 128, 64);
        prm.tile[1][i] = i < A_W1 ? mk(((i ^ 4) & 7) * 8192, 4, 8, tn.TA1 + i * tn.DA1, i < 4 ? 2 : 0, 32 * ((i ^ 2) & 3), 0, 4, 128, (i & 2) ? 64 : -64)
                       : i < A_W2 ? mk(i * 8192, 5, 8, tn.T3 + (i - A_W1) * tn.DA2, 0, 64 * (i - A_W1), 1, 0, 0, 320)
                                  : mk(OFF_W2 + f * 8192, 6, 8, 0, -24, 256 * f, 2, 1, 0, 0);
    }
    make_map(enc, &prm.m[0], d_in[2], 4096, MD, 32, 2);
    make_map(enc, &prm.m[1], d_in[3], 4096, DC, 32, 2);
    make_map(enc, &prm.m[2], d_in[4], 4096, DC, 32, 2);
    make_map(enc, &prm.m[3], d_in[5], MD, 4096, 32, 2);
    make_map(enc, &prm.m[4], d_in[1], DC, SK, 32, 2);
    make_map(enc, &prm.m[5], d_in[7], FF, MD, 64, 1);
    make_map(enc, &prm.m[6], d_in[8], MD, FF, 256, 1, 16);
    fused_kernel<<<NCTA, NTHREADS, SMEM_BYTES>>>((const __nv_bfloat16*)d_in[2], prm);
}
```

```cpp
#include <cuda_runtime.h>
#include <cuda_bf16.h>
#include <cuda.h>
#include <stddef.h>
#include <stdint.h>
#include <stdlib.h>
#include <math.h>

namespace {

typedef unsigned long long u64;
constexpr int MD = 640, DC = 512, SK = 4096, FF = 1728;
constexpr int NCTA = 128;
constexpr int NCOMP = 512;
constexpr int NTHREADS = NCOMP + 128;
constexpr int SPIN_MAX = 1 << 20;
constexpr int CAP = 15;

#define TV(n, d) (d)
#define TP(i, d) (d)
#define D_TQ0 4270
#define D_TQ 4450
#define D_TS 6360
#define D_LB 1890
#define D_LS 1600
#define D_PH 200
#define D_SKEW 140
#define D_TR 9080
#define D_TH 8380
#define D_PW 3300
#define T_Q0 TP(0, D_TQ0)
#define T_Q TP(1, D_TQ)
#define T_S TP(2, D_TS)
#define T_LB TP(3, D_LB)
#define T_LS TP(4, D_LS)
#define T_PH TP(5, D_PH)
#define T_SKEW TP(6, D_SKEW)
#define T_R TP(7, D_TR)
#define T_H TP(8, D_TH)
#define T_PW TP(9, D_PW)

constexpr int OFF_WUK = 0, OFF_WUV = 65536, OFF_WO = 131072;
constexpr int OFF_C = 0, OFF_W1 = 65536, OFF_W2 = OFF_W1 + 40960;
constexpr int OFF_Q = OFF_W2 + 57344, OFF_PIN = OFF_Q + 16384, OFF_POWN = OFF_PIN + 5120,
              OFF_SREM = OFF_POWN + 5120, OFF_OT = OFF_SREM + 4096;
constexpr int OFF_XS = 212992;
constexpr int OFF_EX0 = OFF_XS + 2560;
constexpr int OFF_EX1 = OFF_EX0 + 1024;
constexpr int OFF_O = OFF_EX1 + 1024;
constexpr int OFF_SC = OFF_O + 4224;
constexpr int OFF_LSUM = OFF_SC + 256;
constexpr int OFF_TL = OFF_LSUM + 512;
constexpr int OFF_BAR = OFF_TL + 256;
enum { B_X = 0, B_EX0 = 1, B_EX1 = 2, B_EX2 = 3, B_W = 4, B_M = 5, B_R = 6, B_T = 7, B_COUNT = B_T + 36 };
constexpr int SMEM_BYTES = OFF_BAR + B_COUNT * 8 + 1024;
static_assert(SMEM_BYTES <= 232448 && OFF_OT + 32 * 528 <= OFF_XS, "smem");
enum { P_WQ = 0, P_WUK = 10, P_WUV = 18, P_WO = 26, P_END = 36, A_C = 0, A_W1 = 8, A_W2 = 13, A_END = 19 };
enum { BAR_ALL = 1, BAR_MAX = 2, BAR_L = 4, BAR_WG = 5  , BAR_Q = 9   };

struct Scratch {
    u64 x2[64][32][64];
    uint32_t x4[40][64][16];
    u64 x1[64][64];
    u64 st[2][64][32][2];
    uint32_t xh[FF];
    unsigned int epoch;
};
__device__ __align__(1024) Scratch g_scr;
constexpr uint32_t G_X2 = offsetof(Scratch, x2), G_X4 = offsetof(Scratch, x4), G_X1 = offsetof(Scratch, x1),
                   G_ST = offsetof(Scratch, st), G_XH = offsetof(Scratch, xh), G_EPOCH = offsetof(Scratch, epoch);

struct Params {
    const __nv_bfloat16* x;
    const __nv_bfloat16* gw;
    __nv_bfloat16* out;
    int tp[10];
    uint4 tile[2][36];
    CUtensorMap m[7];
};

#define TLT(i, th)

#define DEVI __device__ __forceinline__
#define F(x) __uint_as_float(x)
#define FULL 0xffffffffu
DEVI float bf_lo(uint32_t w) { return F(w << 16); }
DEVI float bf_hi(uint32_t w) { return F(w & 0xffff0000u); }
DEVI float bf_round(float v) { return __bfloat162float(__float2bfloat16_rn(v)); }
DEVI uint32_t pack_bf(float lo, float hi) { uint32_t r; asm("cvt.rn.bf16x2.f32 %0, %1, %2;" : "=r"(r) : "f"(hi), "f"(lo)); return r; }
DEVI float ex2(float v) { float r; asm("ex2.approx.ftz.f32 %0, %1;" : "=f"(r) : "f"(v)); return r; }
DEVI int f2ord(int b) { return b ^ ((b >> 31) & 0x7fffffff); }
DEVI float ord2f(int b) { return __int_as_float(f2ord(b)); }
DEVI float shx(float v, int m) { return __shfl_xor_sync(FULL, v, m); }
DEVI uint32_t opq(uint32_t v) { return __shfl_sync(FULL, v, threadIdx.x & 31); }
DEVI uint32_t tag_word(uint32_t w, uint32_t tag) { return (w & ~1u) | tag; }

DEVI uint32_t lds32(uint32_t a) { uint32_t v; asm volatile("ld.shared.u32 %0, [%1];" : "=r"(v) : "r"(a) : "memory"); return v; }
DEVI float ldsf(uint32_t a) { return F(lds32(a)); }
DEVI uint2 lds64(uint32_t a) { uint2 v; asm volatile("ld.shared.v2.u32 {%0,%1}, [%2];" : "=r"(v.x), "=r"(v.y) : "r"(a) : "memory"); return v; }
DEVI uint4 lds128(uint32_t a) {
    uint4 v; asm volatile("ld.shared.v4.u32 {%0,%1,%2,%3}, [%4];" : "=r"(v.x), "=r"(v.y), "=r"(v.z), "=r"(v.w) : "r"(a) : "memory"); return v;
}
DEVI void sts32(uint32_t a, uint32_t v) { asm volatile("st.shared.u32 [%0], %1;" :: "r"(a), "r"(v) : "memory"); }
DEVI void sts64(uint32_t a, uint32_t x, uint32_t y) { asm volatile("st.shared.v2.u32 [%0], {%1,%2};" :: "r"(a), "r"(x), "r"(y) : "memory"); }
DEVI void sts128(uint32_t a, const uint4& v) { asm volatile("st.shared.v4.u32 [%0], {%1,%2,%3,%4};" :: "r"(a), "r"(v.x), "r"(v.y), "r"(v.z), "r"(v.w) : "memory"); }

DEVI void st_word(char* p, uint32_t v) { asm volatile("st.relaxed.gpu.global.u32 [%0], %1;" :: "l"(p), "r"(v) : "memory"); }
DEVI uint32_t ld_word(const char* p) { uint32_t v; asm volatile("ld.relaxed.gpu.global.u32 %0, [%1];" : "=r"(v) : "l"(p) : "memory"); return v; }
DEVI uint4 ld_word4(const char* p) {
    uint4 v; asm volatile("ld.relaxed.gpu.global.v4.u32 {%0,%1,%2,%3}, [%4];" : "=r"(v.x), "=r"(v.y), "=r"(v.z), "=r"(v.w) : "l"(p) : "memory"); return v;
}
DEVI void st_pkt(char* p, uint32_t lo, uint32_t hi) {
    asm volatile("{.reg .b64 v; mov.b64 v, {%1,%2}; st.relaxed.gpu.global.b64 [%0], v;}" :: "l"(p), "r"(lo), "r"(hi) : "memory");
}
DEVI void st_pkt2(char* p, const uint4& v) {
    asm volatile("{.reg .b64 a,b; mov.b64 a, {%1,%2}; mov.b64 b, {%3,%4}; st.relaxed.gpu.global.v2.b64 [%0], {a,b};}"
                 :: "l"(p), "r"(v.x), "r"(v.y), "r"(v.z), "r"(v.w) : "memory");
}
DEVI uint2 ld_pkt(const char* p) {
    uint2 v; asm volatile("{.reg .b64 v; ld.relaxed.gpu.global.b64 v, [%2]; mov.b64 {%0,%1}, v;}" : "=r"(v.x), "=r"(v.y) : "l"(p) : "memory"); return v;
}
DEVI uint4 ld_pkt2(const char* p) {
    uint4 v; asm volatile("{.reg .b64 a,b; ld.relaxed.gpu.global.v2.b64 {a,b}, [%4]; mov.b64 {%0,%1}, a; mov.b64 {%2,%3}, b;}"
                          : "=r"(v.x), "=r"(v.y), "=r"(v.z), "=r"(v.w) : "l"(p) : "memory"); return v;
}
DEVI bool stale(uint32_t untagged_or) { return __any_sync(FULL, untagged_or & 1u); }
DEVI uint4 poll_pkt2(const char* p, uint32_t tag) {
    uint4 s;
#pragma unroll 1
    for (int it = 0; it < SPIN_MAX; ++it) {
        s = ld_pkt2(p); s.x ^= tag; s.z ^= tag;
        if (!stale(s.x | s.z)) break;
        __nanosleep(100);
    }
    return s;
}
DEVI uint4 poll_word4(const char* p, uint32_t tag, bool active) {
    uint4 s = make_uint4(0u, 0u, 0u, 0u);
#pragma unroll 1
    for (int it = 0; it < SPIN_MAX; ++it) {
        if (active) { s = ld_word4(p); s.x ^= tag; s.y ^= tag; s.z ^= tag; s.w ^= tag; }
        if (!stale(s.x | s.y | s.z | s.w)) break;
    }
    return s;
}

DEVI uint32_t now_ns() { uint32_t v; asm volatile("mov.u32 %0, %%globaltimer_lo;" : "=r"(v) :: "memory"); return v; }
DEVI void wait_until(uint32_t when) {
    asm volatile("{\n.reg .pred p;\n.reg .s32 l;\nLT:\nmov.u32 l, %%globaltimer_lo;\nsub.s32 l, %0, l;\nsetp.gt.s32 p, l, 300;\n@p nanosleep.u32 100;\n"
                 "setp.gt.s32 p, l, 0;\n@p bra.uni LT;\n}" :: "r"(when) : "memory");
}
DEVI void mbar_wait(uint32_t bar) {
    asm volatile("{\n.reg .pred p;\nLW:\nmbarrier.try_wait.parity.shared::cta.b64 p, [%0], 0;\n@!p bra.uni LW;\n}" :: "r"(bar) : "memory");
}
DEVI void mbar_wait2(uint32_t bar0, uint32_t bar1) {
    asm volatile("{\n.reg .pred p, q;\nLW:\nmbarrier.try_wait.parity.shared::cta.b64 p, [%0], 0;\n"
                 "mbarrier.try_wait.parity.shared::cta.b64 q, [%1], 0;\nand.pred p, p, q;\n@!p bra.uni LW;\n}" :: "r"(bar0), "r"(bar1) : "memory");
}
DEVI void mbar_wait4(uint32_t bar) {
    asm volatile("{\n.reg .pred p, q, s, t;\nLW:\nmbarrier.try_wait.parity.shared::cta.b64 p, [%0], 0;\nmbarrier.try_wait.parity.shared::cta.b64 q, [%0+8], 0;\n"
                 "mbarrier.try_wait.parity.shared::cta.b64 s, [%0+16], 0;\nmbarrier.try_wait.parity.shared::cta.b64 t, [%0+24], 0;\n"
                 "and.pred p, p, q;\nand.pred s, s, t;\nand.pred p, p, s;\n@!p bra.uni LW;\n}" :: "r"(bar) : "memory");
}
DEVI bool mbar_test2(uint32_t bar) {
    uint32_t v;
    asm volatile("{.reg .pred p, q; mbarrier.test_wait.parity.shared::cta.b64 p, [%1], 0; mbarrier.test_wait.parity.shared::cta.b64 q, [%1+8], 0;"
                 " and.pred p, p, q; selp.u32 %0, 1, 0, p;}" : "=r"(v) : "r"(bar) : "memory");
    return __all_sync(FULL, v);
}
DEVI void mbar_init(uint32_t bar, uint32_t n) { asm volatile("mbarrier.init.shared::cta.b64 [%0], %1;" :: "r"(bar), "r"(n) : "memory"); }
DEVI void mbar_arrive(uint32_t bar) { asm volatile("mbarrier.arrive.shared::cta.b64 _, [%0];" :: "r"(bar) : "memory"); }
DEVI void expect_tx(uint32_t bar, uint32_t bytes) {
    asm volatile("mbarrier.arrive.expect_tx.relaxed.cta.shared::cta.b64 _, [%0], %1;" :: "r"(bar), "r"(bytes) : "memory");
}
DEVI void bar_sync(int id, int n) { asm volatile("bar.sync %0, %1;" :: "r"(id), "r"(n) : "memory"); }
DEVI void bar_arrive(int id, int n) { asm volatile("bar.arrive %0, %1;" :: "r"(id), "r"(n) : "memory"); }
DEVI uint32_t peer_addr(uint32_t a, uint32_t rank) { uint32_t r; asm("mapa.shared::cluster.u32 %0, %1, %2;" : "=r"(r) : "r"(a), "r"(rank)); return r; }
DEVI void st_async(uint32_t dst, uint32_t v, uint32_t bar) {
    asm volatile("st.async.shared::cluster.mbarrier::complete_tx::bytes.b32 [%0], %1, [%2];" :: "r"(dst), "r"(v), "r"(bar) : "memory");
}
DEVI void fence_async() { asm volatile("fence.proxy.async.shared::cta;" ::: "memory"); }

DEVI void ldsm4(uint32_t* r, uint32_t a) {
    asm volatile("ldmatrix.sync.aligned.m8n8.x4.shared.b16 {%0,%1,%2,%3}, [%4];" : "=r"(r[0]), "=r"(r[1]), "=r"(r[2]), "=r"(r[3]) : "r"(a) : "memory");
}
DEVI void ldsm4t(uint32_t* r, uint32_t a) {
    asm volatile("ldmatrix.sync.aligned.m8n8.x4.trans.shared.b16 {%0,%1,%2,%3}, [%4];" : "=r"(r[0]), "=r"(r[1]), "=r"(r[2]), "=r"(r[3]) : "r"(a) : "memory");
}
DEVI void stsm4t(uint32_t a, const uint32_t* r) {
    asm volatile("stmatrix.sync.aligned.m8n8.x4.trans.shared.b16 [%0], {%1,%2,%3,%4};" :: "r"(a), "r"(r[0]), "r"(r[1]), "r"(r[2]), "r"(r[3]) : "memory");
}
DEVI void mma_w(float* c, const uint32_t* a, uint32_t b0, uint32_t b1) {
    asm volatile("mma.sync.aligned.m16n8k16.row.col.f32.bf16.bf16.f32 {%0,%1,%2,%3}, {%4,%5,%6,%7}, {%8,%9}, {%0,%1,%2,%3};"
                 : "+f"(c[0]), "+f"(c[1]), "+f"(c[2]), "+f"(c[3]) : "r"(a[0]), "r"(a[1]), "r"(a[2]), "r"(a[3]), "r"(b0), "r"(b1));
}
DEVI void wgmma_rs(float* d, const uint32_t* a, u64 desc) {
    asm volatile("wgmma.mma_async.sync.aligned.m64n32k16.f32.bf16.bf16 {%0,%1,%2,%3,%4,%5,%6,%7,%8,%9,%10,%11,%12,%13,%14,%15}, "
                 "{%16,%17,%18,%19}, %20, 1, 1, 1, 0;"
                 : "+f"(d[0]), "+f"(d[1]), "+f"(d[2]), "+f"(d[3]), "+f"(d[4]), "+f"(d[5]), "+f"(d[6]), "+f"(d[7]),
                   "+f"(d[8]), "+f"(d[9]), "+f"(d[10]), "+f"(d[11]), "+f"(d[12]), "+f"(d[13]), "+f"(d[14]), "+f"(d[15])
                 : "r"(a[0]), "r"(a[1]), "r"(a[2]), "r"(a[3]), "l"(desc) : "memory");
}
DEVI void wg_fence() { asm volatile("wgmma.fence.sync.aligned;" ::: "memory"); }
DEVI void wg_commit() { asm volatile("wgmma.commit_group.sync.aligned;" ::: "memory"); }
DEVI void wg_wait() { asm volatile("wgmma.wait_group.sync.aligned 0;" ::: "memory"); }
DEVI u64 sdesc(uint32_t addr) { return (u64)((addr & 0x3FFFFu) >> 4) | (1ull << 16) | (64ull << 32) | (1ull << 62); }
template <int N> DEVI void zero(float* d) {
#pragma unroll
    for (int i = 0; i < N; ++i) { d[i] = 0.f; asm volatile("" : "+f"(d[i])); }
}

__global__ void __cluster_dims__(2, 1, 1) __launch_bounds__(NTHREADS, 1)
fused_kernel(const char* __restrict__ wq, char* __restrict__ scr, const __grid_constant__ Params prm) {
    extern __shared__ __align__(1024) unsigned char sm_raw[];
    uint32_t sbase = ((uint32_t)__cvta_generic_to_shared(sm_raw) + 1023u) & ~1023u;
    asm volatile("" : "+r"(sbase));
    const uint32_t t = threadIdx.x, lane = t & 31;
    {
        const uint32_t b = blockIdx.x;
        const char* src = wq + ((320 * (b & 1) + ((t >> 2) & 96) + ((t >> 4) & 7)) * 8192 + (b >> 1) * 256 + (t & 15) * 16);
        const uint32_t dst = sbase + OFF_WO + (t >> 7) * 8192 + (t & 8) * 512 + (t & 112) * 8 + (((t ^ (t >> 4)) & 7) << 4);
        asm volatile("{.reg .pred p; setp.eq.u32 p, %2, 0;\n"
                     "@p cp.async.cg.shared.global [%0], [%1], 16;\n"
                     "@p cp.async.cg.shared.global [%0+1024], [%1+65536], 16;\n"
                     "@p cp.async.cg.shared.global [%0+2048], [%1+131072], 16;\n"
                     "@p cp.async.cg.shared.global [%0+3072], [%1+196608], 16;}"
                     :: "r"(dst), "l"(src), "r"((t >> 9) | (b >> 6)) : "memory");
    }
    const uint32_t t0 = now_ns();
    const uint32_t wb = __shfl_sync(FULL, (t >> 5) | (blockIdx.x << 8), 0);
    const uint32_t warp = wb & 255, r = (wb >> 8) & 1, id = (wb >> 9) & 31, me = (wb >> 8) & 63;
    const bool roleA = wb >> 14, ffn = id < 27;
    const uint32_t bars = sbase + OFF_BAR, tb = bars + 8 * B_T;

    if (warp >= 16) {
        const uint32_t k = warp - 16;
        const u64 mapbase = reinterpret_cast<u64>(&prm.m[0]);
        if (lane == 0) {
            asm volatile("prefetch.tensormap [%0];" :: "l"(mapbase + 128 * (roleA ? 3 + k : k)) : "memory");
            if (k == 3) {
#pragma unroll
                for (int i = 0; i < B_T; ++i) mbar_init(bars + 8 * i, i == B_W ? 32 : 1);
                expect_tx(bars + 8 * B_X, 2560);
                asm volatile("cp.async.bulk.shared::cluster.global.mbarrier::complete_tx::bytes [%0], [%1], 1280, [%2];"
                             :: "r"(sbase + OFF_XS), "l"(prm.x), "r"(bars + 8 * B_X) : "memory");
                asm volatile("cp.async.bulk.shared::cluster.global.mbarrier::complete_tx::bytes [%0], [%1], 1280, [%2];"
                             :: "r"(sbase + OFF_XS + 1280), "l"(prm.gw), "r"(bars + 8 * B_X) : "memory");
                expect_tx(bars + 8 * B_EX0, roleA ? 4096 : 1024);
                expect_tx(bars + 8 * B_EX1, roleA ? 1024 : 512);
                if (roleA) expect_tx(bars + 8 * B_EX2, 4096);
                expect_tx(bars + 8 * B_M, 128);
                expect_tx(bars + 8 * B_R, 512);
            } else {
#pragma unroll
                for (int i = 0; i < 12; ++i) mbar_init(tb + 8 * (k + 3 * i), i < 2 && !roleA && k + 3 * i < 4 ? 128 : 1);
            }
            asm volatile("fence.mbarrier_init.release.cluster;" ::: "memory");
        }
        __syncwarp();
        asm volatile("barrier.cluster.arrive.relaxed.aligned;" ::: "memory");
        asm volatile("setmaxnreg.dec.sync.aligned.u32 32;");
        if (k == 3) {
            const uint32_t tag = opq((ld_word(scr + G_EPOCH) & 1u) ^ 1u);
            if (roleA) {
                char* const mdst = scr + (G_ST + lane * 1024 + id * 16 + r * 8);
#pragma unroll
                for (int i = 0; i < 4; ++i) st_pkt(mdst + (i & 1) * 512 + (i >> 1) * 32768, tag ^ 1u, 0u);
                sts32(sbase + OFF_POWN + 4096 + 4 * lane, 0x80000000u);
                mbar_wait(bars + 8 * B_X);
                float s = 0.f;
#pragma unroll 1
                for (int i = 0; i < 10; ++i) {
                    uint32_t pr;
                    asm("mul.rn.bf16x2 %0, %1, %2;" : "=r"(pr) : "r"(lds32(sbase + OFF_XS + lane * 4 + 128 * i)), "r"(lds32(sbase + OFF_XS + 1280 + lane * 4 + 128 * i)));
                    s += bf_lo(pr) + bf_hi(pr);
                }
#pragma unroll 1
                for (int j = 16; j > 0; j >>= 1) s += shx(s, j);
                const float ga = bf_round(__fdividef(1.0f, 1.0f + __expf(-bf_round(s))));
                if (lane == 0) sts128(sbase + OFF_EX0, make_uint4(__float_as_uint(ga), __float_as_uint(bf_round(1.0f - ga)), 0xffff0000u, 0u));
                const uint32_t pdst = opq(peer_addr(sbase + OFF_PIN, r ^ 1)), pbar = opq(peer_addr(bars, r ^ 1));
                bar_arrive(BAR_Q, 416);
                bar_sync(BAR_Q + 1, 416);
                const uint32_t zero_ = lds32(sbase + OFF_EX0 + 12);
                const uint32_t ts = now_ns() + zero_;
                st_pkt(mdst, tag, ts); st_pkt(mdst + 512, tag, ts);
                bar_sync(BAR_MAX, 160);
                const int mo = (int)lds32(sbase + OFF_POWN + 4096 + 4 * lane);
                st_async(pdst + 4096 + 4 * lane, mo, pbar + 8 * B_M);
                bar_sync(BAR_ALL, NCOMP + 32);
                if (lane == 0)
                    asm volatile("cp.async.bulk.shared::cluster.shared::cta.mbarrier::complete_tx::bytes [%0], [%1], 4096, [%2];"
                                 :: "r"(pdst), "r"(sbase + OFF_POWN), "r"(pbar + 8 * B_EX2) : "memory");
                mbar_wait(bars + 8 * B_M);
                const int mi = (int)lds32(sbase + OFF_PIN + 4096 + 4 * lane);
                const float mm = ord2f(max(mo, mi));
                sts64(sbase + OFF_SC + 8 * lane, __float_as_uint(ex2(ord2f(mo) - mm)), __float_as_uint(ex2(ord2f(mi) - mm)));
                mbar_arrive(bars + 8 * B_W);
                bar_sync(BAR_L, 160);
                const uint32_t la = sbase + OFF_LSUM + 4 * lane;
                const uint32_t lw = tag_word(__float_as_uint((ldsf(la) + ldsf(la + 128)) + (ldsf(la + 256) + ldsf(la + 384))), tag);
                st_pkt(mdst + 32768, lw, mo); st_pkt(mdst + 33280, lw, mo);
            } else {
                const char* ssrc = scr + (G_ST + me * 512 + lane * 16);
                wait_until(t0 + T_S);
                uint4 sv = poll_pkt2(ssrc, tag);
                const uint32_t last = t0 + __reduce_max_sync(FULL, max((int)(sv.y - t0), (int)(sv.w - t0)));
                if (lane == 0) { sts32(sbase + OFF_LSUM, last + T_LB); mbar_arrive(bars + 8 * B_EX2); }
                wait_until(last + T_LS);
                sv = poll_pkt2(ssrc + 32768, tag);
                const float mg = ord2f(__reduce_max_sync(FULL, max((int)sv.y, (int)sv.w)));
                const float e0 = ex2(ord2f((int)sv.y) - mg), e1 = ex2(ord2f((int)sv.w) - mg);
                float lg = e0 * F(sv.x) + e1 * F(sv.z);
#pragma unroll
                for (int j = 16; j > 0; j >>= 1) lg += shx(lg, j);
                sts32(sbase + OFF_SC + 4 * lane, __float_as_uint(__fdividef(fmaxf(e0, e1), lg)));
                mbar_arrive(bars + 8 * B_W);
            }
            TLT(19, 608);
            return;
        }
        const uint32_t total = roleA ? (me >= 24 ? A_END : A_W2) : P_END;
        const uint32_t tp = t0 + ((me * T_PH) >> 6);
#define MONITOR()
#pragma unroll 1
        for (uint32_t i = roleA ? k : (k ? k + 3 : 6); i < total; i += 3) {
            if (roleA && !ffn && i >= A_W1 && i < A_W2) continue;
            const uint4 e = prm.tile[roleA][i];
            const uint32_t blk = (int)(short)e.z + (e.w & 255u) * id + ((e.w >> 8) & 255u) * r;
            const uint32_t row = (e.z >> 16) + 32 * (((e.w >> 16) & 255u) * id + ((int)e.w >> 24) * r);
            if (!roleA && i >= CAP) mbar_wait(tb + 8 * (i - CAP));
            if (!roleA && i - P_WO < 3) {
                asm volatile("barrier.cluster.wait.aligned;" ::: "memory");
                mbar_wait(bars + 8 * B_EX0);
            }
            if (lane == 0) expect_tx(tb + 8 * i, (e.x >> 24) << 10);
            while ((int)(now_ns() - tp) < (int)e.y) { __nanosleep(40); MONITOR(); }
            if (lane == 0) {
                asm volatile("cp.async.bulk.tensor.3d.shared::cluster.global.mbarrier::complete_tx::bytes [%0], [%1, {%5, %2, %3}], [%4];"
                             :: "r"(sbase + (e.x & 0xfffffu)), "l"(mapbase + 128 * ((e.x >> 20) & 7u)), "r"(row), "r"(blk), "r"(tb + 8 * i), "r"(0) : "memory");
            }
            __syncwarp();
        }
        return;
    }

    asm volatile("setmaxnreg.inc.sync.aligned.u32 112;");
    const uint32_t epoch = ld_word(scr + G_EPOCH);
    asm volatile("barrier.cluster.arrive.relaxed.aligned;" ::: "memory");
    asm volatile("barrier.cluster.wait.aligned;" ::: "memory");
    const uint32_t tag = opq((epoch & 1u) ^ 1u);
    const uint32_t g = lane >> 2, tq = lane & 3, wg = warp >> 2;
    const uint32_t tsw = opq(sbase + ((lane & 7) + (lane >> 4) * 8) * 128 + (((2 * (warp & 3) + ((lane >> 3) & 1)) ^ (lane & 7)) << 4));
    const uint32_t nsw = opq(sbase + (warp >> 1) * 8192 + (16 * (warp & 1) + (lane & 15)) * 128 + (((lane >> 4) ^ (lane & 7)) << 4));
    const uint32_t vsw = opq(sbase + (lane >> 3) * 16);
    float d[16];

    if (roleA) {
        const uint32_t xo = opq(G_X2 + (2 * ((t & 127) >> 3) + r) * 16384 + id * 512 + wg * 128 + (lane & 7) * 16);
        const uint32_t oa = opq(sbase + OFF_OT + ((lane & 7) + (lane >> 4) * 8) * 528 + warp * 32 + ((lane >> 3) & 1) * 16);
        const uint32_t ob = opq(sbase + OFF_OT + ((t & 127) >> 3) * 528 + wg * 128 + (lane & 7) * 16);
        const uint32_t pa = opq(tsw + OFF_C + (wg >> 1) * 32768 + (wg & 1) * 4096);
        if (ffn && warp == 0) st_word(scr + (G_XH + me * 128 + lane * 4), tag ^ 1u);
        wait_until(t0 + T_PW + 40 * warp);
        st_pkt2(scr + xo, make_uint4(tag ^ 1u, 0u, tag ^ 1u, 0u));
        st_pkt2(scr + xo + 32 * 16384, make_uint4(tag ^ 1u, 0u, tag ^ 1u, 0u));
        uint32_t fa[64];
        float d2[16];
        if (warp < 8) {
            const uint32_t so = sbase + OFF_SREM + (t & 127) * 16;
            const uint32_t sx = opq(wg ? so : peer_addr(so, r ^ 1));
            zero<16>(d);
#pragma unroll
            for (int cp = 1; cp >= 0; --cp) {
                mbar_wait(tb + 8 * (A_C + 4 * (1 - cp)) + 8 * (warp >> 1));
#pragma unroll
                for (int k = 0; k < 8; ++k) ldsm4(fa + 32 * cp + 4 * k, (nsw ^ ((k & 3) << 5)) + OFF_C + cp * 32768 + (k >> 2) * 4096);
            }
            if (wg) mbar_wait4(tb + 8 * (A_C + 4));
            TLT(1, 224);
            bar_sync(BAR_Q + wg, 416);
            if (wg) { const uint32_t c = clock(); while ((uint32_t)clock() - c < (uint32_t)T_SKEW) { } }
            TLT(2, 0);
            wg_fence();
#pragma unroll
            for (int ks = 0; ks < 16; ++ks) wgmma_rs(d, fa + 4 * ks, sdesc(sbase + OFF_Q) + (ks >> 2) * 256 + (ks & 3) * 2);
            wg_commit();
            wg_wait();
            TLT(17, 128);
            if (wg == 0) {
                const uint32_t rbar = peer_addr(bars + 8 * B_EX0, r ^ 1);
#pragma unroll
                for (int i = 0; i < 2; ++i)
                    asm volatile("st.async.shared::cluster.mbarrier::complete_tx::bytes.v4.b32 [%0], {%1,%2,%3,%4}, [%5];"
                                 :: "r"(sx + i * 2048), "r"(pack_bf(d[8 * i], d[8 * i + 1])), "r"(pack_bf(d[8 * i + 2], d[8 * i + 3])),
                                    "r"(pack_bf(d[8 * i + 4], d[8 * i + 5])), "r"(pack_bf(d[8 * i + 6], d[8 * i + 7])), "r"(rbar) : "memory");
                TLT(3, 0);
            }
            d2[0] = F(sx);
        } else {
            const uint32_t hq = 4 * (warp - 8) + (lane >> 3);
            const char* src = scr + opq(G_X1 + (2 * hq + r) * 512 + (lane & 7) * 16);
            const uint32_t qa = opq(sbase + OFF_Q + hq * 128 + (((lane ^ hq) & 7) << 4));
            uint4 v[4];
            wait_until(t0 + T_Q0);
#pragma unroll
            for (int k = 0; k < 3; ++k) v[k] = ld_pkt2(src + 128 * k);
            wait_until(t0 + T_Q);
            TLT(8, 256);
            v[3] = ld_pkt2(src + 384);
            uint32_t old = 0;
#pragma unroll
            for (int k = 0; k < 4; ++k) {
                v[k].x ^= tag; v[k].z ^= tag;
                old |= v[k].x | v[k].z;
                sts128(qa + k * 4096, v[k]);
            }
            if (stale(old)) {
#pragma unroll 1
                for (int k = 0; k < 4; ++k) sts128(qa + k * 4096, poll_pkt2(src + 128 * k, tag));
            }
            fence_async();
            bar_arrive(BAR_Q, 416);
            bar_arrive(BAR_Q + 1, 416);
            TLT(9, 256);
        }
        if (wg != 1) mbar_wait4(tb + 8 * A_C + 16 * (~wg & 2));
#pragma unroll
        for (int ks = 0; ks < 8; ++ks) ldsm4t(fa + 4 * ks, pa + (ks >> 1) * 8192 + (ks & 1) * 2048);
        if (wg == 1) {
            const uint32_t sx = __float_as_uint(d2[0]);
            const bool b4 = lane & 16, b3 = lane & 8, b2 = lane & 4;
            const uint32_t ha = sbase + 4 * (8 * (g >> 1) + 2 * tq + (g & 1));
            float u[8];
            uint32_t pk[8];
            mbar_wait(bars + 8 * B_EX0);
            TLT(18, 128);
#pragma unroll
            for (int i = 0; i < 2; ++i) {
                const uint4 o = lds128(sx + i * 2048);
                d[8 * i] += bf_lo(o.x); d[8 * i + 1] += bf_hi(o.x); d[8 * i + 2] += bf_lo(o.y); d[8 * i + 3] += bf_hi(o.y);
                d[8 * i + 4] += bf_lo(o.z); d[8 * i + 5] += bf_hi(o.z); d[8 * i + 6] += bf_lo(o.w); d[8 * i + 7] += bf_hi(o.w);
            }
#pragma unroll
            for (int i = 0; i < 8; ++i) u[i] = fmaxf(d[4 * (i >> 1) + (i & 1)], d[4 * (i >> 1) + (i & 1) + 2]);
#pragma unroll
            for (int i = 0; i < 4; ++i) u[i] = fmaxf(b4 ? u[i + 4] : u[i], shx(b4 ? u[i] : u[i + 4], 16));
#pragma unroll
            for (int i = 0; i < 2; ++i) u[i] = fmaxf(b3 ? u[i + 2] : u[i], shx(b3 ? u[i] : u[i + 2], 8));
            asm volatile("red.shared.max.s32 [%0], %1;" :: "r"(ha + OFF_POWN + 4096),
                         "r"(f2ord(__float_as_int(fmaxf(b2 ? u[1] : u[0], shx(b2 ? u[0] : u[1], 4))))) : "memory");
            bar_sync(BAR_MAX, 160);
            TLT(13, 128);
#pragma unroll
            for (int j = 0; j < 4; ++j) {
                const uint2 mi = lds64(sbase + OFF_POWN + 4096 + 32 * j + 8 * tq);
                const float m0 = ord2f((int)mi.x), m1 = ord2f((int)mi.y);
                pk[2 * j] = pack_bf(ex2(d[4 * j] - m0), ex2(d[4 * j + 1] - m1));
                pk[2 * j + 1] = pack_bf(ex2(d[4 * j + 2] - m0), ex2(d[4 * j + 3] - m1));
            }
            stsm4t(tsw + OFF_POWN, pk);
            stsm4t(tsw + OFF_POWN + 2048, pk + 4);
            fence_async();
            bar_arrive(BAR_ALL, NCOMP + 32);
            const uint32_t hm = lds32(sbase + OFF_EX0 + 8);
#pragma unroll
            for (int j = 0; j < 4; ++j) {
                u[2 * j] = F((pk[2 * j] << 16) & hm) + bf_lo(pk[2 * j + 1]);
                u[2 * j + 1] = F(pk[2 * j] & hm) + bf_hi(pk[2 * j + 1]);
            }
#pragma unroll
            for (int i = 0; i < 4; ++i) u[i] = (b4 ? u[i + 4] : u[i]) + shx(b4 ? u[i] : u[i + 4], 16);
#pragma unroll
            for (int i = 0; i < 2; ++i) u[i] = (b3 ? u[i + 2] : u[i]) + shx(b3 ? u[i] : u[i + 2], 8);
            sts32(ha + OFF_LSUM + (warp & 3) * 128, __float_as_uint((b2 ? u[1] : u[0]) + shx(b2 ? u[0] : u[1], 4)));
            bar_arrive(BAR_L, 160);
        }
        zero<16>(d); zero<16>(d2);
        bar_sync(wg == 1 ? BAR_WG + 1 : BAR_ALL, wg == 1 ? 128 : NCOMP + 32);
        TLT(5, 256);
        wg_fence();
#pragma unroll
        for (int ks = 0; ks < 4; ++ks) wgmma_rs(d, fa + 16 + 4 * ks, sdesc(sbase + OFF_POWN) + ks * 2);
        mbar_wait2(bars + 8 * B_EX2, bars + 8 * B_W);
        TLT(4, 256);
        wg_fence();
#pragma unroll
        for (int ks = 0; ks < 4; ++ks) wgmma_rs(d2, fa + 4 * ks, sdesc(sbase + OFF_PIN) + ks * 2);
        wg_commit();
        {
            uint4 ab[4];
            uint32_t ok[8];
#pragma unroll
            for (int j = 0; j < 4; ++j) ab[j] = lds128(sbase + OFF_SC + 64 * j + 16 * tq);
            wg_wait();
#pragma unroll
            for (int i = 0; i < 8; ++i)
                ok[i] = pack_bf(F(ab[i >> 1].x) * d[2 * i] + F(ab[i >> 1].y) * d2[2 * i], F(ab[i >> 1].z) * d[2 * i + 1] + F(ab[i >> 1].w) * d2[2 * i + 1]);
            stsm4t(oa, ok);
            stsm4t(oa + 16 * 528, ok + 4);
            bar_sync(BAR_WG + wg, 128);
            TLT(14, 128);
#pragma unroll
            for (int i = 0; i < 2; ++i) {
                uint4 v = lds128(ob + i * 16 * 528);
                v.x = tag_word(v.x, tag); v.z = tag_word(v.z, tag);
                st_pkt2(scr + xo + i * (32 * 16384), v);
            }
        }
        TLT(6, 128);
        if (ffn) {
            uint32_t a[20], b[12];
            const uint32_t xa = vsw + OFF_XS + 640 * r + wg * 160;
            ldsm4(b, xa); ldsm4(b + 4, xa + 64); ldsm4(b + 8, xa + 128);
            mbar_wait2(tb + 8 * A_W1 + 8 * wg, tb + 8 * (A_W1 + 1) + 8 * wg);
#pragma unroll
            for (int k = 0; k < 5; ++k) ldsm4t(a + 4 * k, tsw + OFF_W1 + wg * 10240 + k * 2048);
            zero<8>(d);
#pragma unroll
            for (int k = 0; k < 5; ++k) mma_w(d + 4 * (k & 1), a + 4 * k, b[2 * k], b[2 * k + 1]);
            const uint32_t rank = (warp >> 1) & 1;
            if (tq < 2)
                st_async(peer_addr(sbase + OFF_EX1 + ((4 * r + wg) * 32 + 16 * (warp & 1) + g + 8 * tq) * 4, rank),
                         __float_as_uint(tq ? d[2] + d[6] : d[0] + d[4]), peer_addr(bars + 8 * B_EX1, rank));
            if (warp == 0) {
                mbar_wait(bars + 8 * B_EX1);
                float h = 0.f;
#pragma unroll
                for (int i = 0; i < 8; ++i) h += ldsf(sbase + OFF_EX1 + lane * 4 + 128 * i);
                h = bf_round(h);
                st_word(scr + (G_XH + me * 128 + lane * 4), __float_as_uint(bf_round(__fdividef(h, 1.0f + __expf(-h)))) | tag);
            }
        }
        TLT(7, 0);
        if (me >= 24) {
            const float gg = ldsf(sbase + OFF_EX0 + (warp >> 3) * 4);
            if (warp < 8) {
                const char* rsrc = scr + opq(G_X4 + (me - 24) * 4096 + t * 16);
                const uint32_t rw = opq(sbase + OFF_O + (warp * 16 + 4 * tq + (lane >> 3)) * 4);
                wait_until(t0 + T_R);
                const uint4 rv = poll_word4(rsrc, tag, true);
                const bool b4 = lane & 16, b3 = lane & 8;
                const float y0 = F(b4 ? rv.z : rv.x) + shx(F(b4 ? rv.x : rv.z), 16), y1 = F(b4 ? rv.w : rv.y) + shx(F(b4 ? rv.y : rv.w), 16);
                float y = (b3 ? y1 : y0) + shx(b3 ? y0 : y1, 8);
                y += shx(y, 4);
                sts32(rw, __float_as_uint(gg * y));
            } else {
                const uint32_t w8 = warp - 8, wrow = 16 * w8 + (lane & 7) + (lane >> 4) * 8;
                const uint32_t wa = opq(sbase + OFF_W2 + wrow * 64 + ((((lane >> 3) & 1) ^ ((wrow >> 1) & 3)) << 4));
                const uint32_t rw = opq(peer_addr(sbase + OFF_O + (((tq >> 1) == r ? warp : warp + 8) * 16 + g + 8 * (tq & 1)) * 4, tq >> 1));
                wait_until(t0 + T_H);
                const uint4 hv = poll_word4(scr + (G_XH + (864 * r + 128 * g + 16 * w8 + 4 * tq) * 4), tag, 128 * g + 16 * w8 < 864);
                sts64(sbase + OFF_Q + w8 * 256 + lane * 8, __byte_perm(hv.x, hv.y, 0x7632), __byte_perm(hv.z, hv.w, 0x7632));
                __syncwarp();
                uint32_t b[16];
#pragma unroll
                for (int j = 0; j < 4; ++j) ldsm4(b + 4 * j, vsw + OFF_Q + w8 * 256 + j * 64);
                TLT(12, 256);
                zero<16>(d);
#pragma unroll
                for (int jj = 0; jj < 3; ++jj) {
                    uint32_t a[24];
                    mbar_wait2(tb + 8 * (A_W2 + 2 * jj), tb + 8 * (A_W2 + 2 * jj + 1));
#pragma unroll
                    for (int k = 0; k < 4; ++k) ldsm4t(a + 4 * k, (wa ^ ((k & 1) << 5)) + (2 * jj + (k >> 1)) * 8192);
                    if (jj == 2 && w8 < 6) { ldsm4t(a + 16, wa + 6 * 8192); ldsm4t(a + 20, (wa ^ 32) + 6 * 8192); }
#pragma unroll
                    for (int k = 0; k < 4; ++k) mma_w(d + 4 * k, a + 4 * k, b[4 * jj + 2 * (k >> 1)], b[4 * jj + 2 * (k >> 1) + 1]);
                    if (jj == 2 && w8 < 6) { mma_w(d, a + 16, b[12], b[13]); mma_w(d + 4, a + 20, b[12], b[13]); }
                }
                const float o = gg * (tq == 0 ? d[0] + d[8] : (tq == 1 ? d[2] + d[10] : (tq == 2 ? d[4] + d[12] : d[6] + d[14])));
                if ((tq >> 1) == r) asm volatile("st.shared::cluster.f32 [%0], %1;" :: "r"(rw), "f"(o) : "memory");
                else st_async(rw, __float_as_uint(o), peer_addr(bars + 8 * B_R, r ^ 1));
                TLT(16, 256);
            }
            if (warp != 15) bar_arrive(BAR_Q, NCOMP);
            else {
                const uint32_t rp = opq(sbase + OFF_O + ((lane >> 4) * 192 + (lane & 15)) * 4);
                char* const op = reinterpret_cast<char*>(prm.out) + opq(32 * (me - 24) + 2 * lane);
                mbar_wait(bars + 8 * B_R);
                bar_sync(BAR_Q, NCOMP);
                float z = 0.f, z1 = 0.f, z2 = 0.f;
#pragma unroll
                for (int i = 0; i < 4; ++i) { z += ldsf(rp + 192 * i); z1 += ldsf(rp + 192 * i + 64); z2 += ldsf(rp + 192 * i + 128); }
                z += z1 + z2;
                z += shx(z, 16);
                if (lane < 16) *reinterpret_cast<__nv_bfloat16*>(op) = __float2bfloat16_rn(z);
                if (me == 24 && lane == 0) st_word(scr + G_EPOCH, epoch + 1u);
                TLT(11, 480);
            }
        }
    } else {
        asm volatile("cp.async.mbarrier.arrive.noinc.shared::cta.b64 [%0];" :: "r"(tb + 8 * wg) : "memory");
        const uint32_t oo = opq(G_X4 + (warp + 16 * (tq >> 1)) * 4096 + me * 64 + (g + 8 * (tq & 1)) * 4);
        const uint32_t qo = opq(G_X1 + me * 512 + (4 * warp + 2 * tq + (lane >> 4)) * 8);
        if ((lane & 14) == 0) st_pkt(scr + qo, tag ^ 1u, 0u);
        st_word(scr + oo, tag ^ 1u);
        if (tq < 2 && warp < 8) st_word(scr + oo + 32 * 4096, tag ^ 1u);
        uint32_t a[32], b[16];
        if (warp < 8) {
            const uint32_t rdst = opq(peer_addr(sbase + OFF_EX0 + (r * 128 + 16 * warp + g + 8 * (tq & 1)) * 4, tq >> 1));
            mbar_wait(bars + 8 * B_X);
            zero<8>(d);
#pragma unroll 1
            for (int kb = 0; kb < 10; ++kb) {
                ldsm4(b, vsw + OFF_XS + 640 * r + 64 * kb);
                mbar_wait(tb + 8 * (P_WQ + kb));
                ldsm4t(a, tsw + OFF_WO + wg * 4096 + kb * 8192); ldsm4t(a + 4, tsw + OFF_WO + 2048 + wg * 4096 + kb * 8192);
                mma_w(d, a, b[0], b[1]); mma_w(d + 4, a + 4, b[2], b[3]);
            }
            st_async(rdst, __float_as_uint((tq & 1) ? d[2] + d[6] : d[0] + d[4]), peer_addr(bars + 8 * B_EX0, tq >> 1));
        }
        TLT(1, 0);
        {
            mbar_wait(bars + 8 * B_EX0);
            const uint4 q0 = lds128(sbase + OFF_EX0 + lane * 16), q1 = lds128(sbase + OFF_EX0 + 512 + lane * 16);
            sts64(sbase + OFF_O + lane * 8, pack_bf(F(q0.x) + F(q1.x), F(q0.y) + F(q1.y)), pack_bf(F(q0.z) + F(q1.z), F(q0.w) + F(q1.w)));
            __syncwarp();
#pragma unroll
            for (int k = 0; k < 4; ++k) ldsm4(b + 4 * k, vsw + OFF_O + 64 * k);
            TLT(2, 0);
            zero<16>(d);
            mbar_wait(tb + 8 * P_WUK + 8 * (warp >> 1));
#pragma unroll
            for (int k = 0; k < 8; ++k) ldsm4(a + 4 * k, (nsw ^ ((k & 3) << 5)) + OFF_WUK + (k >> 2) * 4096);
#pragma unroll
            for (int k = 0; k < 8; ++k) mma_w(d + 4 * (k & 3), a + 4 * k, b[2 * k], b[2 * k + 1]);
            const float sc = 0.08838834764831845f * 1.4426950408889634f;
            const float v = ((tq & 1) ? (d[2] + d[6]) + (d[10] + d[14]) : (d[0] + d[4]) + (d[8] + d[12])) * sc;
            const uint32_t w = pack_bf(v, __shfl_down_sync(FULL, v, 4));
            const uint32_t w2 = __shfl_down_sync(FULL, w, 8);
            if ((lane & 14) == 0) st_pkt(scr + qo, tag_word(w, tag), w2);
        }
        TLT(3, 480);
        const uint32_t rank = wg & 1;
        const char* src = scr + opq(G_X2 + me * 16384 + (warp >> 1) * 2048 + (warp & 1) * 256 + lane * 8);
        const uint32_t rdst = opq(peer_addr(sbase + OFF_EX1 + (2 * r + (warp >> 3)) * 144 + (16 * (warp & 3) + g + 8 * (tq & 1)) * 2, rank));
        const uint32_t rbar = opq(peer_addr(bars + 8 * B_EX1, rank));
        const uint32_t ow = opq(sbase + OFF_O + (warp >> 1) * 528 + (warp & 1) * 256 + lane * 8);
        const uint32_t ol = opq(vsw + OFF_O + (lane & 7) * 528 + (warp >> 3) * 256);
        const uint32_t cl = opq(vsw + OFF_EX1 + (lane & 3) * 144);
        const uint32_t wm = opq(tsw + OFF_WO + (warp >> 3) * 16384 + rank * 4096), ob = tb + 8 * P_WO + 16 * (warp >> 3);
        mbar_wait4(tb + 8 * P_WUV + 32 * (warp >> 3));
#pragma unroll
        for (int k = 0; k < 8; ++k) ldsm4t(a + 4 * k, tsw + OFF_WUV + (warp >> 3) * 32768 + rank * 4096 + (k >> 1) * 8192 + (k & 1) * 2048);
        zero<16>(d);
        mbar_wait(bars + 8 * B_EX2);
        TLT(4, 0);
        wait_until(lds32(sbase + OFF_LSUM));
        TLT(14, 0);
        uint2 v[4];
#pragma unroll
        for (int i = 0; i < 4; ++i) v[i] = ld_pkt(src + 512 * i);
        uint32_t w0[16];
#define LOAD_WO(dst_, i_) do { _Pragma("unroll") for (int k = 0; k < 4; ++k) ldsm4t((dst_) + 4 * k, wm + (i_) * 32768 + (k >> 1) * 8192 + (k & 1) * 2048); } while (0)
        const bool early = mbar_test2(ob);
        if (early) LOAD_WO(w0, 0);
        mbar_wait(bars + 8 * B_W);
        const uint4 wn = lds128(sbase + OFF_SC + 16 * (warp >> 1));
#pragma unroll 1
        for (int it = 0; it < SPIN_MAX; ++it) {
#pragma unroll
            for (int i = 0; i < 4; ++i) v[i].x ^= tag;
            if (!stale(v[0].x | v[1].x | v[2].x | v[3].x)) break;
#pragma unroll
            for (int i = 0; i < 4; ++i) v[i] = ld_pkt(src + 512 * i);
            TLT(20, 0);
        }
        TLT(5, 0);
#define MRG(f, h) (F(wn.x) * h(v[0].f) + F(wn.y) * h(v[1].f) + F(wn.z) * h(v[2].f) + F(wn.w) * h(v[3].f))
        sts64(ow, pack_bf(MRG(x, bf_lo), MRG(x, bf_hi)), pack_bf(MRG(y, bf_lo), MRG(y, bf_hi)));
        bar_sync(BAR_ALL, NCOMP);
        TLT(6, 0);
#pragma unroll
        for (int k = 0; k < 4; ++k) ldsm4(b + 4 * k, ol + 64 * k);
#pragma unroll
        for (int k = 0; k < 8; ++k) mma_w(d + 4 * (k & 3), a + 4 * k, b[2 * k], b[2 * k + 1]);
        {
            const float c0 = ((d[0] + d[1]) + (d[4] + d[5])) + ((d[8] + d[9]) + (d[12] + d[13]));
            const float c1 = ((d[2] + d[3]) + (d[6] + d[7])) + ((d[10] + d[11]) + (d[14] + d[15]));
            float c = ((tq & 1) ? c1 : c0) + shx((tq & 1) ? c0 : c1, 1);
            c += shx(c, 2);
            const uint32_t cw = pack_bf(c, __shfl_down_sync(FULL, c, 4));
            if ((lane & 6) == 0) st_async(rdst, cw, rbar);
        }
        TLT(15, 0);
        if (!early) { mbar_wait2(ob, ob + 8); LOAD_WO(w0, 0); }
        mbar_wait2(ob + 32, ob + 40);
        LOAD_WO(a, 1);
        const bool third = warp < 8 && mbar_test2(ob + 64);
        if (third) LOAD_WO(a + 16, 2);
        zero<16>(d);
        mbar_wait(bars + 8 * B_EX1);
        TLT(7, 0);
        ldsm4(b, cl); ldsm4(b + 4, cl + 64);
#pragma unroll
        for (int k = 0; k < 4; ++k) {
            mma_w(d + 4 * (k & 1), w0 + 4 * k, b[2 * k], b[2 * k + 1]);
            mma_w(d + 8 + 4 * (k & 1), a + 4 * k, b[2 * k], b[2 * k + 1]);
        }
        {
            const float lo = tq < 2 ? (d[0] + d[1]) + (d[4] + d[5]) : (d[8] + d[9]) + (d[12] + d[13]);
            const float hi = tq < 2 ? (d[2] + d[3]) + (d[6] + d[7]) : (d[10] + d[11]) + (d[14] + d[15]);
            st_word(scr + oo, tag_word(__float_as_uint(((tq & 1) ? hi : lo) + shx((tq & 1) ? lo : hi, 1)), tag));
        }
        if (warp < 8) {
            if (!third) { mbar_wait2(ob + 64, ob + 72); LOAD_WO(a + 16, 2); }
            zero<16>(d);
#pragma unroll
            for (int k = 0; k < 4; ++k) mma_w(d + 4 * k, a + 16 + 4 * k, b[2 * k], b[2 * k + 1]);
            const float lo = ((d[0] + d[1]) + (d[4] + d[5])) + ((d[8] + d[9]) + (d[12] + d[13]));
            const float hi = ((d[2] + d[3]) + (d[6] + d[7])) + ((d[10] + d[11]) + (d[14] + d[15]));
            const float o = ((tq & 1) ? hi : lo) + shx((tq & 1) ? lo : hi, 1);
            if (tq < 2) st_word(scr + oo + 32 * 4096, tag_word(__float_as_uint(o), tag));
        }
        TLT(10, 0);
    }
}

typedef const __nv_bfloat16* BP;
__device__ float f_q[4096], f_qa[32 * DC], f_p[32 * SK], f_lat[32 * DC], f_ctx[4096], f_h[FF];
DEVI float bf(BP p, size_t i) { return __bfloat162float(p[i]); }
__global__ void fb_in(BP x, BP wq, BP w1) {
    const int n = blockIdx.x * blockDim.x + threadIdx.x;
    if (n >= 4096 + FF) return;
    float s = 0.f;
    for (int m = 0; m < MD; ++m) s += bf(x, m) * (n < 4096 ? bf(wq, (size_t)m * 4096 + n) : bf(w1, (size_t)m * FF + n - 4096));
    s = bf_round(s);
    if (n < 4096) f_q[n] = s; else f_h[n - 4096] = bf_round(s / (1.0f + expf(-s)));
}
__global__ void fb_qabs(BP wuk) {
    const int n = blockIdx.x * blockDim.x + threadIdx.x, h = n / DC, c = n % DC;
    float s = 0.f;
    for (int k = 0; k < 128; ++k) s += bf(wuk, ((size_t)c * 32 + h) * 128 + k) * f_q[h * 128 + k];
    f_qa[n] = s * 0.08838834764831845f;
}
__global__ void fb_attn(BP ckv) {
    __shared__ float red[512];
    const int h = blockIdx.x, t = threadIdx.x;
    float m = -INFINITY;
    for (int k = t; k < SK; k += 512) {
        float s = 0.f;
        for (int c = 0; c < DC; ++c) s += bf(ckv, (size_t)k * DC + c) * f_qa[h * DC + c];
        f_p[h * SK + k] = s; m = fmaxf(m, s);
    }
    red[t] = m; __syncthreads();
    for (int i = 0; i < 512; ++i) m = fmaxf(m, red[i]);
    __syncthreads();
    float l = 0.f;
    for (int k = t; k < SK; k += 512) { const float e = expf(f_p[h * SK + k] - m); f_p[h * SK + k] = e; l += e; }
    red[t] = l; __syncthreads();
    l = 0.f;
    for (int i = 0; i < 512; ++i) l += red[i];
    float a = 0.f;
    for (int k = 0; k < SK; ++k) a += f_p[h * SK + k] * bf(ckv, (size_t)k * DC + t);
    f_lat[h * DC + t] = a / l;
}
__global__ void fb_ctx(BP wuv) {
    const int n = blockIdx.x * blockDim.x + threadIdx.x;
    float s = 0.f;
    for (int c = 0; c < DC; ++c) s += f_lat[(n >> 7) * DC + c] * bf(wuv, (size_t)c * 4096 + n);
    f_ctx[n] = bf_round(s);
}
__global__ void fb_out(BP x, BP gw, BP wo, BP w2, __nv_bfloat16* out) {
    const int n = blockIdx.x * blockDim.x + threadIdx.x;
    float s = 0.f, a = 0.f, b = 0.f;
    for (int m = 0; m < MD; ++m) s += bf_round(bf(x, m) * bf(gw, m));
    for (int k = 0; k < 4096; ++k) a += f_ctx[k] * bf(wo, (size_t)k * MD + n);
    for (int k = 0; k < FF; ++k) b += f_h[k] * bf(w2, (size_t)k * MD + n);
    const float g = bf_round(1.0f / (1.0f + expf(-bf_round(s))));
    out[n] = __float2bfloat16_rn(g * a + bf_round(1.0f - g) * b);
}

typedef CUresult (*EncodeFn)(CUtensorMap*, CUtensorMapDataType, cuuint32_t, void*, const cuuint64_t*, const cuuint64_t*,
                             const cuuint32_t*, const cuuint32_t*, CUtensorMapInterleave, CUtensorMapSwizzle,
                             CUtensorMapL2promotion, CUtensorMapFloatOOBfill);

void make_map(EncodeFn enc, CUtensorMap* m, void* base, uint64_t cols, uint64_t rows, uint32_t brows, uint32_t bblk, uint32_t bw = 64) {
    cuuint64_t dims[3] = {bw, rows, cols / bw};
    cuuint64_t strides[2] = {cols * 2, bw * 2};
    cuuint32_t box[3] = {bw, brows, bblk};
    cuuint32_t es[3] = {1, 1, 1};
    enc(m, CU_TENSOR_MAP_DATA_TYPE_BFLOAT16, 3, base, dims, strides, box, es, CU_TENSOR_MAP_INTERLEAVE_NONE,
        bw == 64 ? CU_TENSOR_MAP_SWIZZLE_128B : CU_TENSOR_MAP_SWIZZLE_64B, CU_TENSOR_MAP_L2_PROMOTION_NONE, CU_TENSOR_MAP_FLOAT_OOB_FILL_NONE);
}

}

extern "C" void kernel_launch(void* const* d_in, const int* in_sizes, int n_in, void* d_out, int out_size) {
    (void)in_sizes; (void)n_in; (void)out_size;
    static EncodeFn enc = nullptr;
    static void* scr = nullptr;
    static int mode = 0;
    if (!mode) {
        cudaFuncSetAttribute(fused_kernel, cudaFuncAttributeMaxDynamicSharedMemorySize, SMEM_BYTES);
        cudaGetSymbolAddress(&scr, g_scr);
        void* fn = nullptr;
        cudaDriverEntryPointQueryResult qr;
        cudaGetDriverEntryPoint("cuTensorMapEncodeTiled", &fn, cudaEnableDefault, &qr);
        enc = (EncodeFn)fn;
        cudaLaunchConfig_t cfg = {};
        cudaLaunchAttribute at;
        at.id = cudaLaunchAttributeClusterDimension;
        at.val.clusterDim.x = 2; at.val.clusterDim.y = 1; at.val.clusterDim.z = 1;
        cfg.gridDim = dim3(NCTA); cfg.blockDim = dim3(NTHREADS); cfg.dynamicSmemBytes = SMEM_BYTES; cfg.attrs = &at; cfg.numAttrs = 1;
        int nclusters = 0;
        const cudaError_t e = cudaOccupancyMaxActiveClusters(&nclusters, fused_kernel, &cfg);
        (void)cudaGetLastError();
        mode = (enc && e == cudaSuccess && nclusters >= NCTA / 2 && !TV(FALLBACK, 0)) ? 1 : 2;
    }
    if (mode == 2) {
        fb_in<<<(4096 + FF + 63) / 64, 64>>>((BP)d_in[0], (BP)d_in[2], (BP)d_in[7]);
        fb_qabs<<<32 * DC / 128, 128>>>((BP)d_in[3]);
        fb_attn<<<32, 512>>>((BP)d_in[1]);
        fb_ctx<<<4096 / 64, 64>>>((BP)d_in[4]);
        fb_out<<<MD / 32, 32>>>((BP)d_in[0], (BP)d_in[9], (BP)d_in[5], (BP)d_in[8], (__nv_bfloat16*)d_out);
        return;
    }
    Params prm;
    prm.x = (const __nv_bfloat16*)d_in[0];
    prm.gw = (const __nv_bfloat16*)d_in[9];
    prm.out = (__nv_bfloat16*)d_out;
    const int tp[10] = {TV(TQ0, D_TQ0), TV(TQ, D_TQ), TV(TS, D_TS), TV(LB, D_LB), TV(LS, D_LS), TV(PH, D_PH), TV(SKEW, D_SKEW), TV(TR, D_TR), TV(TR1, D_TH), TV(PW, D_PW)};
    for (int i = 0; i < 10; ++i) prm.tp[i] = tp[i];
    const int TP1 = TV(TP1, 2320), DD1 = TV(DD1, 180);
    const int TA1 = TV(TA1, 2650), DA1 = TV(DA1, 140);
    const int T3 = TV(T3, 4100), DP2 = TV(DP2, 232), DA2 = TV(DA2, 395), DP3 = TV(DP3, 180);
    const int TW2 = TV(TW2, 7710), DW2 = TV(DW2, 95);
    for (int i = 0; i < 36; ++i) {
        auto mk = [&](int dst, int map, int kb, int when, int blk, int row, int blki, int blkr, int rowi, int rowr) {
            if ((TV(NOLOAD, 0) >> map) & 1) { kb = 0; when = 0; }
            return make_uint4(dst | map << 20 | kb << 24, when, (blk & 0xffff) | row << 16, blki | blkr << 8 | rowi / 32 << 16 | (unsigned)(rowr / 32) << 24);
        };
        const int j = i - P_WO, f = i - A_W2;
        prm.tile[0][i] = i < P_WUK ? mk(OFF_WO + i * 8192, 0, 8, TP1 + (i - 17) * DD1, 0, 32 * i, 2, 0, 0, 320)
                       : i < P_WUV ? mk(OFF_WUK + (i - P_WUK) * 8192, 1, 8, TP1 + (i - 17) * DD1, 0, 32 * (i - P_WUK), 2, 0, 0, 256)
                       : i < P_WO  ? mk(OFF_WUV + (i - P_WUV) * 8192, 2, 8, T3 + (i - P_WUV) * DP2, 0, 32 * (i - P_WUV), 2, 0, 0, 256)
                                   : mk(OFF_WO + j * 8192, 3, 8, T3 + 8 * DP2 + j * DP3, j & ~1, 32 * (j & 1), 0, 0, 128, 64);
        prm.tile[1][i] = i < A_W1 ? mk(OFF_C + ((i ^ 4) & 7) * 8192, 4, 8, TA1 + i * DA1, i < 4 ? 2 : 0, 32 * ((i ^ 2) & 3), 0, 4, 128, (i & 2) ? 64 : -64)
                       : i < A_W2 ? mk(OFF_W1 + (i - A_W1) * 8192, 5, 8, T3 + (i - A_W1) * DA2, 0, 64 * (i - A_W1), 1, 0, 0, 320)
                                  : mk(OFF_W2 + f * 9216, 6, 9, TW2 + f * DW2, -12, 144 * f, 1, 0, 0, 864);
    }
    make_map(enc, &prm.m[0], d_in[2], 4096, MD, 32, 2);
    make_map(enc, &prm.m[1], d_in[3], 4096, DC, 32, 2);
    make_map(enc, &prm.m[2], d_in[4], 4096, DC, 32, 2);
    make_map(enc, &prm.m[3], d_in[5], MD, 4096, 32, 2);
    make_map(enc, &prm.m[4], d_in[1], DC, SK, 32, 2);
    make_map(enc, &prm.m[5], d_in[7], FF, MD, 64, 1);
    make_map(enc, &prm.m[6], d_in[8], MD, FF, 144, 1, 32);
    fused_kernel<<<NCTA, NTHREADS, SMEM_BYTES>>>((const char*)d_in[2], (char*)scr, prm);
}
```

```cpp
#include <cuda_runtime.h>
#include <cuda_bf16.h>
#include <cuda.h>
#include <stddef.h>
#include <stdint.h>
#include <math.h>

namespace {

typedef unsigned long long u64;
constexpr int MD = 640, DC = 512, SK = 4096, FF = 1728;
constexpr int NCTA = 128;
constexpr int NCOMP = 512;
constexpr int NTHREADS = NCOMP + 128;
constexpr int SPIN_MAX = 1 << 20;
constexpr int CAP = 15;

constexpr int T_Q0 = 4240;
constexpr int T_Q = 4430;
constexpr int T_S = 6290;
constexpr int T_LB = 1930;
constexpr int T_LS = 1640;
constexpr int T_PH = 200;
constexpr int T_SKEW = 140;
constexpr int T_R = 9050;
constexpr int T_H = 8310;
constexpr int T_PW = 3230;

constexpr int OFF_WUK = 0, OFF_WUV = 65536, OFF_WO = 131072;
constexpr int OFF_C = 0, OFF_W1 = 65536, OFF_W2 = OFF_W1 + 40960;
constexpr int OFF_Q = OFF_W2 + 57344, OFF_PIN = OFF_Q + 16384, OFF_POWN = OFF_PIN + 5120,
              OFF_SREM = OFF_POWN + 5120, OFF_OT = OFF_SREM + 4096;
constexpr int OFF_XS = 212992;
constexpr int OFF_EX0 = OFF_XS + 2560;
constexpr int OFF_EX1 = OFF_EX0 + 1024;
constexpr int OFF_O = OFF_EX1 + 1024;
constexpr int OFF_SC = OFF_O + 4224;
constexpr int OFF_LSUM = OFF_SC + 256;
constexpr int OFF_BAR = OFF_LSUM + 768;
enum { B_X = 0, B_EX0 = 1, B_EX1 = 2, B_EX2 = 3, B_W = 4, B_M = 5, B_R = 6, B_T = 7, B_COUNT = B_T + 36 };
constexpr int SMEM_BYTES = OFF_BAR + B_COUNT * 8 + 1024;
static_assert(SMEM_BYTES <= 232448 && OFF_OT + 32 * 528 <= OFF_XS, "smem");
enum { P_WQ = 0, P_WUK = 10, P_WUV = 18, P_WO = 26, P_END = 36, A_C = 0, A_W1 = 8, A_W2 = 13, A_END = 19 };
enum { BAR_ALL = 1, BAR_MAX = 2, BAR_L = 4, BAR_WG = 5  , BAR_Q = 9   };

struct Scratch {
    u64 x2[64][32][64];
    uint32_t x4[40][64][16];
    u64 x1[64][64];
    u64 st[2][64][32][2];
    uint32_t xh[FF];
    unsigned int epoch;
};
__device__ __align__(1024) Scratch g_scr;
constexpr uint32_t G_X2 = offsetof(Scratch, x2), G_X4 = offsetof(Scratch, x4), G_X1 = offsetof(Scratch, x1),
                   G_ST = offsetof(Scratch, st), G_XH = offsetof(Scratch, xh), G_EPOCH = offsetof(Scratch, epoch);

struct Params {
    const __nv_bfloat16* x;
    const __nv_bfloat16* gw;
    __nv_bfloat16* out;
    uint4 tile[2][36];
    CUtensorMap m[7];
};

#define DEVI __device__ __forceinline__
#define F(x) __uint_as_float(x)
#define FULL 0xffffffffu
DEVI float bf_lo(uint32_t w) { return F(w << 16); }
DEVI float bf_hi(uint32_t w) { return F(w & 0xffff0000u); }
DEVI float bf_round(float v) { return __bfloat162float(__float2bfloat16_rn(v)); }
DEVI uint32_t pack_bf(float lo, float hi) { uint32_t r; asm("cvt.rn.bf16x2.f32 %0, %1, %2;" : "=r"(r) : "f"(hi), "f"(lo)); return r; }
DEVI float ex2(float v) { float r; asm("ex2.approx.ftz.f32 %0, %1;" : "=f"(r) : "f"(v)); return r; }
DEVI int f2ord(int b) { return b ^ ((b >> 31) & 0x7fffffff); }
DEVI float ord2f(int b) { return __int_as_float(f2ord(b)); }
DEVI float shx(float v, int m) { return __shfl_xor_sync(FULL, v, m); }
DEVI uint32_t opq(uint32_t v) { return __shfl_sync(FULL, v, threadIdx.x & 31); }
DEVI uint32_t tag_word(uint32_t w, uint32_t tag) { return (w & ~1u) | tag; }

DEVI uint32_t lds32(uint32_t a) { uint32_t v; asm volatile("ld.shared.u32 %0, [%1];" : "=r"(v) : "r"(a) : "memory"); return v; }
DEVI float ldsf(uint32_t a) { return F(lds32(a)); }
DEVI uint2 lds64(uint32_t a) { uint2 v; asm volatile("ld.shared.v2.u32 {%0,%1}, [%2];" : "=r"(v.x), "=r"(v.y) : "r"(a) : "memory"); return v; }
DEVI uint4 lds128(uint32_t a) {
    uint4 v; asm volatile("ld.shared.v4.u32 {%0,%1,%2,%3}, [%4];" : "=r"(v.x), "=r"(v.y), "=r"(v.z), "=r"(v.w) : "r"(a) : "memory"); return v;
}
DEVI void sts32(uint32_t a, uint32_t v) { asm volatile("st.shared.u32 [%0], %1;" :: "r"(a), "r"(v) : "memory"); }
DEVI void sts64(uint32_t a, uint32_t x, uint32_t y) { asm volatile("st.shared.v2.u32 [%0], {%1,%2};" :: "r"(a), "r"(x), "r"(y) : "memory"); }
DEVI void sts128(uint32_t a, const uint4& v) { asm volatile("st.shared.v4.u32 [%0], {%1,%2,%3,%4};" :: "r"(a), "r"(v.x), "r"(v.y), "r"(v.z), "r"(v.w) : "memory"); }

DEVI void st_word(char* p, uint32_t v) { asm volatile("st.relaxed.gpu.global.u32 [%0], %1;" :: "l"(p), "r"(v) : "memory"); }
DEVI uint32_t ld_word(const char* p) { uint32_t v; asm volatile("ld.relaxed.gpu.global.u32 %0, [%1];" : "=r"(v) : "l"(p) : "memory"); return v; }
DEVI uint4 ld_word4(const char* p) {
    uint4 v; asm volatile("ld.relaxed.gpu.global.v4.u32 {%0,%1,%2,%3}, [%4];" : "=r"(v.x), "=r"(v.y), "=r"(v.z), "=r"(v.w) : "l"(p) : "memory"); return v;
}
DEVI void st_pkt(char* p, uint32_t lo, uint32_t hi) {
    asm volatile("{.reg .b64 v; mov.b64 v, {%1,%2}; st.relaxed.gpu.global.b64 [%0], v;}" :: "l"(p), "r"(lo), "r"(hi) : "memory");
}
DEVI void st_pkt2(char* p, const uint4& v) {
    asm volatile("{.reg .b64 a,b; mov.b64 a, {%1,%2}; mov.b64 b, {%3,%4}; st.relaxed.gpu.global.v2.b64 [%0], {a,b};}"
                 :: "l"(p), "r"(v.x), "r"(v.y), "r"(v.z), "r"(v.w) : "memory");
}
DEVI uint2 ld_pkt(const char* p) {
    uint2 v; asm volatile("{.reg .b64 v; ld.relaxed.gpu.global.b64 v, [%2]; mov.b64 {%0,%1}, v;}" : "=r"(v.x), "=r"(v.y) : "l"(p) : "memory"); return v;
}
DEVI uint4 ld_pkt2(const char* p) {
    uint4 v; asm volatile("{.reg .b64 a,b; ld.relaxed.gpu.global.v2.b64 {a,b}, [%4]; mov.b64 {%0,%1}, a; mov.b64 {%2,%3}, b;}"
                          : "=r"(v.x), "=r"(v.y), "=r"(v.z), "=r"(v.w) : "l"(p) : "memory"); return v;
}
DEVI bool stale(uint32_t untagged_or) { return __any_sync(FULL, untagged_or & 1u); }
DEVI uint4 poll_pkt2(const char* p, uint32_t tag) {
    uint4 s;
#pragma unroll 1
    for (int it = 0; it < SPIN_MAX; ++it) {
        s = ld_pkt2(p); s.x ^= tag; s.z ^= tag;
        if (!stale(s.x | s.z)) break;
        __nanosleep(100);
    }
    return s;
}
DEVI uint4 poll_word4(const char* p, uint32_t tag, bool active) {
    uint4 s = make_uint4(0u, 0u, 0u, 0u);
#pragma unroll 1
    for (int it = 0; it < SPIN_MAX; ++it) {
        if (active) { s = ld_word4(p); s.x ^= tag; s.y ^= tag; s.z ^= tag; s.w ^= tag; }
        if (!stale(s.x | s.y | s.z | s.w)) break;
    }
    return s;
}

DEVI uint32_t now_ns() { uint32_t v; asm volatile("mov.u32 %0, %%globaltimer_lo;" : "=r"(v) :: "memory"); return v; }
DEVI void wait_until(uint32_t when) {
    asm volatile("{\n.reg .pred p;\n.reg .s32 l;\nLT:\nmov.u32 l, %%globaltimer_lo;\nsub.s32 l, %0, l;\nsetp.gt.s32 p, l, 300;\n@p nanosleep.u32 100;\n"
                 "setp.gt.s32 p, l, 0;\n@p bra.uni LT;\n}" :: "r"(when) : "memory");
}
DEVI void mbar_wait(uint32_t bar) {
    asm volatile("{\n.reg .pred p;\nLW:\nmbarrier.try_wait.parity.shared::cta.b64 p, [%0], 0;\n@!p bra.uni LW;\n}" :: "r"(bar) : "memory");
}
DEVI void mbar_wait2(uint32_t bar0, uint32_t bar1) {
    asm volatile("{\n.reg .pred p, q;\nLW:\nmbarrier.try_wait.parity.shared::cta.b64 p, [%0], 0;\n"
                 "mbarrier.try_wait.parity.shared::cta.b64 q, [%1], 0;\nand.pred p, p, q;\n@!p bra.uni LW;\n}" :: "r"(bar0), "r"(bar1) : "memory");
}
DEVI void mbar_wait4(uint32_t bar) {
    asm volatile("{\n.reg .pred p, q, s, t;\nLW:\nmbarrier.try_wait.parity.shared::cta.b64 p, [%0], 0;\nmbarrier.try_wait.parity.shared::cta.b64 q, [%0+8], 0;\n"
                 "mbarrier.try_wait.parity.shared::cta.b64 s, [%0+16], 0;\nmbarrier.try_wait.parity.shared::cta.b64 t, [%0+24], 0;\n"
                 "and.pred p, p, q;\nand.pred s, s, t;\nand.pred p, p, s;\n@!p bra.uni LW;\n}" :: "r"(bar) : "memory");
}
DEVI bool mbar_test2(uint32_t bar) {
    uint32_t v;
    asm volatile("{.reg .pred p, q; mbarrier.test_wait.parity.shared::cta.b64 p, [%1], 0; mbarrier.test_wait.parity.shared::cta.b64 q, [%1+8], 0;"
                 " and.pred p, p, q; selp.u32 %0, 1, 0, p;}" : "=r"(v) : "r"(bar) : "memory");
    return __all_sync(FULL, v);
}
DEVI void mbar_init(uint32_t bar, uint32_t n) { asm volatile("mbarrier.init.shared::cta.b64 [%0], %1;" :: "r"(bar), "r"(n) : "memory"); }
DEVI void mbar_arrive(uint32_t bar) { asm volatile("mbarrier.arrive.shared::cta.b64 _, [%0];" :: "r"(bar) : "memory"); }
DEVI void expect_tx(uint32_t bar, uint32_t bytes) {
    asm volatile("mbarrier.arrive.expect_tx.relaxed.cta.shared::cta.b64 _, [%0], %1;" :: "r"(bar), "r"(bytes) : "memory");
}
DEVI void bar_sync(int id, int n) { asm volatile("bar.sync %0, %1;" :: "r"(id), "r"(n) : "memory"); }
DEVI void bar_arrive(int id, int n) { asm volatile("bar.arrive %0, %1;" :: "r"(id), "r"(n) : "memory"); }
DEVI uint32_t peer_addr(uint32_t a, uint32_t rank) { uint32_t r; asm("mapa.shared::cluster.u32 %0, %1, %2;" : "=r"(r) : "r"(a), "r"(rank)); return r; }
DEVI void st_async(uint32_t dst, uint32_t v, uint32_t bar) {
    asm volatile("st.async.shared::cluster.mbarrier::complete_tx::bytes.b32 [%0], %1, [%2];" :: "r"(dst), "r"(v), "r"(bar) : "memory");
}
DEVI void fence_async() { asm volatile("fence.proxy.async.shared::cta;" ::: "memory"); }

DEVI void ldsm4(uint32_t* r, uint32_t a) {
    asm volatile("ldmatrix.sync.aligned.m8n8.x4.shared.b16 {%0,%1,%2,%3}, [%4];" : "=r"(r[0]), "=r"(r[1]), "=r"(r[2]), "=r"(r[3]) : "r"(a) : "memory");
}
DEVI void ldsm4t(uint32_t* r, uint32_t a) {
    asm volatile("ldmatrix.sync.aligned.m8n8.x4.trans.shared.b16 {%0,%1,%2,%3}, [%4];" : "=r"(r[0]), "=r"(r[1]), "=r"(r[2]), "=r"(r[3]) : "r"(a) : "memory");
}
DEVI void stsm4t(uint32_t a, const uint32_t* r) {
    asm volatile("stmatrix.sync.aligned.m8n8.x4.trans.shared.b16 [%0], {%1,%2,%3,%4};" :: "r"(a), "r"(r[0]), "r"(r[1]), "r"(r[2]), "r"(r[3]) : "memory");
}
DEVI void mma_w(float* c, const uint32_t* a, uint32_t b0, uint32_t b1) {
    asm volatile("mma.sync.aligned.m16n8k16.row.col.f32.bf16.bf16.f32 {%0,%1,%2,%3}, {%4,%5,%6,%7}, {%8,%9}, {%0,%1,%2,%3};"
                 : "+f"(c[0]), "+f"(c[1]), "+f"(c[2]), "+f"(c[3]) : "r"(a[0]), "r"(a[1]), "r"(a[2]), "r"(a[3]), "r"(b0), "r"(b1));
}
DEVI void wgmma_rs(float* d, const uint32_t* a, u64 desc) {
    asm volatile("wgmma.mma_async.sync.aligned.m64n32k16.f32.bf16.bf16 {%0,%1,%2,%3,%4,%5,%6,%7,%8,%9,%10,%11,%12,%13,%14,%15}, "
                 "{%16,%17,%18,%19}, %20, 1, 1, 1, 0;"
                 : "+f"(d[0]), "+f"(d[1]), "+f"(d[2]), "+f"(d[3]), "+f"(d[4]), "+f"(d[5]), "+f"(d[6]), "+f"(d[7]),
                   "+f"(d[8]), "+f"(d[9]), "+f"(d[10]), "+f"(d[11]), "+f"(d[12]), "+f"(d[13]), "+f"(d[14]), "+f"(d[15])
                 : "r"(a[0]), "r"(a[1]), "r"(a[2]), "r"(a[3]), "l"(desc) : "memory");
}
DEVI void wg_fence() { asm volatile("wgmma.fence.sync.aligned;" ::: "memory"); }
DEVI void wg_commit() { asm volatile("wgmma.commit_group.sync.aligned;" ::: "memory"); }
DEVI void wg_wait() { asm volatile("wgmma.wait_group.sync.aligned 0;" ::: "memory"); }
DEVI u64 sdesc(uint32_t addr) { return (u64)((addr & 0x3FFFFu) >> 4) | (1ull << 16) | (64ull << 32) | (1ull << 62); }
template <int N> DEVI void zero(float* d) {
#pragma unroll
    for (int i = 0; i < N; ++i) { d[i] = 0.f; asm volatile("" : "+f"(d[i])); }
}

__global__ void __cluster_dims__(2, 1, 1) __launch_bounds__(NTHREADS, 1)
fused_kernel(const char* __restrict__ wq, char* __restrict__ scr, const __grid_constant__ Params prm) {
    extern __shared__ __align__(1024) unsigned char sm_raw[];
    uint32_t sbase = ((uint32_t)__cvta_generic_to_shared(sm_raw) + 1023u) & ~1023u;
    asm volatile("" : "+r"(sbase));
    const uint32_t t = threadIdx.x, lane = t & 31;
    const uint32_t b = (blockIdx.x + (NCTA - 8)) & (NCTA - 1);
    {
        const char* src = wq + ((320 * (b & 1) + ((t >> 2) & 96) + ((t >> 4) & 7)) * 8192 + (b >> 1) * 256 + (t & 15) * 16);
        const uint32_t dst = sbase + OFF_WO + (t >> 7) * 8192 + (t & 8) * 512 + (t & 112) * 8 + (((t ^ (t >> 4)) & 7) << 4);
        asm volatile("{.reg .pred p; setp.eq.u32 p, %2, 0;\n"
                     "@p cp.async.cg.shared.global [%0], [%1], 16;\n"
                     "@p cp.async.cg.shared.global [%0+1024], [%1+65536], 16;\n"
                     "@p cp.async.cg.shared.global [%0+2048], [%1+131072], 16;\n"
                     "@p cp.async.cg.shared.global [%0+3072], [%1+196608], 16;\n"
                     "@p cp.async.cg.shared.global [%0+32768], [%1+1048576], 16;\n"
                     "@p cp.async.cg.shared.global [%0+33792], [%1+1114112], 16;\n"
                     "@p cp.async.cg.shared.global [%0+34816], [%1+1179648], 16;\n"
                     "@p cp.async.cg.shared.global [%0+35840], [%1+1245184], 16;\n"
                     "}"
                     :: "r"(dst), "l"(src), "r"((t >> 9) | (b >> 6)) : "memory");
    }
    const uint32_t t0 = now_ns();
    const uint32_t wb = __shfl_sync(FULL, (t >> 5) | (b << 8), 0);
    const uint32_t warp = wb & 255, r = (wb >> 8) & 1, id = (wb >> 9) & 31, me = (wb >> 8) & 63;
    const bool roleA = wb >> 14, ffn = id < 27;
    const uint32_t bars = sbase + OFF_BAR, tb = bars + 8 * B_T;

    if (warp >= 16) {
        const uint32_t k = warp - 16;
        const u64 mapbase = reinterpret_cast<u64>(&prm.m[0]);
        if (lane == 0) {
            asm volatile("prefetch.tensormap [%0];" :: "l"(mapbase + 128 * (roleA ? 3 + k : k)) : "memory");
            if (k == 3) {
#pragma unroll
                for (int i = 0; i < B_T; ++i) mbar_init(bars + 8 * i, i == B_W ? 32 : 1);
                expect_tx(bars + 8 * B_X, 2560);
                asm volatile("cp.async.bulk.shared::cluster.global.mbarrier::complete_tx::bytes [%0], [%1], 1280, [%2];"
                             :: "r"(sbase + OFF_XS), "l"(prm.x), "r"(bars + 8 * B_X) : "memory");
                asm volatile("cp.async.bulk.shared::cluster.global.mbarrier::complete_tx::bytes [%0], [%1], 1280, [%2];"
                             :: "r"(sbase + OFF_XS + 1280), "l"(prm.gw), "r"(bars + 8 * B_X) : "memory");
                expect_tx(bars + 8 * B_EX0, roleA ? 4096 : 1024);
                expect_tx(bars + 8 * B_EX1, roleA ? 1024 : 512);
                if (roleA) expect_tx(bars + 8 * B_EX2, 4096);
                expect_tx(bars + 8 * B_M, 128);
                expect_tx(bars + 8 * B_R, 512);
            } else {
#pragma unroll
                for (int i = 0; i < 12; ++i) mbar_init(tb + 8 * (k + 3 * i), i < 3 && !roleA && k + 3 * i < 8 ? 128 : 1);
            }
            asm volatile("fence.mbarrier_init.release.cluster;" ::: "memory");
        }
        __syncwarp();
        asm volatile("barrier.cluster.arrive.relaxed.aligned;" ::: "memory");
        asm volatile("setmaxnreg.dec.sync.aligned.u32 32;");
        if (k == 3) {
            const uint32_t tag = opq((ld_word(scr + G_EPOCH) & 1u) ^ 1u);
            if (roleA) {
                char* const mdst = scr + (G_ST + lane * 1024 + id * 16 + r * 8);
#pragma unroll
                for (int i = 0; i < 4; ++i) st_pkt(mdst + (i & 1) * 512 + (i >> 1) * 32768, tag ^ 1u, 0u);
                sts32(sbase + OFF_POWN + 4096 + 4 * lane, 0x80000000u);
                mbar_wait(bars + 8 * B_X);
                float s = 0.f;
#pragma unroll 1
                for (int i = 0; i < 10; ++i) {
                    uint32_t pr;
                    asm("mul.rn.bf16x2 %0, %1, %2;" : "=r"(pr) : "r"(lds32(sbase + OFF_XS + lane * 4 + 128 * i)), "r"(lds32(sbase + OFF_XS + 1280 + lane * 4 + 128 * i)));
                    s += bf_lo(pr) + bf_hi(pr);
                }
#pragma unroll 1
                for (int j = 16; j > 0; j >>= 1) s += shx(s, j);
                const float ga = bf_round(__fdividef(1.0f, 1.0f + __expf(-bf_round(s))));
                if (lane == 0) sts128(sbase + OFF_EX0, make_uint4(__float_as_uint(ga), __float_as_uint(bf_round(1.0f - ga)), 0xffff0000u, 0u));
                const uint32_t pdst = opq(peer_addr(sbase + OFF_PIN, r ^ 1)), pbar = opq(peer_addr(bars, r ^ 1));
                bar_arrive(BAR_Q, 416);
                bar_sync(BAR_Q + 1, 416);
                const uint32_t zero_ = lds32(sbase + OFF_EX0 + 12);
                const uint32_t ts = now_ns() + zero_;
                st_pkt(mdst, tag, ts); st_pkt(mdst + 512, tag, ts);
                bar_sync(BAR_MAX, 160);
                const int mo = (int)lds32(sbase + OFF_POWN + 4096 + 4 * lane);
                st_async(pdst + 4096 + 4 * lane, mo, pbar + 8 * B_M);
                bar_sync(BAR_ALL, NCOMP + 32);
                if (lane == 0)
                    asm volatile("cp.async.bulk.shared::cluster.shared::cta.mbarrier::complete_tx::bytes [%0], [%1], 4096, [%2];"
                                 :: "r"(pdst), "r"(sbase + OFF_POWN), "r"(pbar + 8 * B_EX2) : "memory");
                mbar_wait(bars + 8 * B_M);
                const int mi = (int)lds32(sbase + OFF_PIN + 4096 + 4 * lane);
                const float mm = ord2f(max(mo, mi));
                sts64(sbase + OFF_SC + 8 * lane, __float_as_uint(ex2(ord2f(mo) - mm)), __float_as_uint(ex2(ord2f(mi) - mm)));
                mbar_arrive(bars + 8 * B_W);
                bar_sync(BAR_L, 160);
                const uint32_t la = sbase + OFF_LSUM + 4 * lane;
                const uint32_t lw = tag_word(__float_as_uint((ldsf(la) + ldsf(la + 128)) + (ldsf(la + 256) + ldsf(la + 384))), tag);
                st_pkt(mdst + 32768, lw, mo); st_pkt(mdst + 33280, lw, mo);
            } else {
                const char* ssrc = scr + (G_ST + me * 512 + lane * 16);
                wait_until(t0 + T_S);
                uint4 sv = poll_pkt2(ssrc, tag);
                const uint32_t last = t0 + __reduce_max_sync(FULL, max((int)(sv.y - t0), (int)(sv.w - t0)));
                if (lane == 0) { sts32(sbase + OFF_LSUM, last + T_LB); mbar_arrive(bars + 8 * B_EX2); }
                wait_until(last + T_LS);
                sv = poll_pkt2(ssrc + 32768, tag);
                const float mg = ord2f(__reduce_max_sync(FULL, max((int)sv.y, (int)sv.w)));
                const float e0 = ex2(ord2f((int)sv.y) - mg), e1 = ex2(ord2f((int)sv.w) - mg);
                float lg = e0 * F(sv.x) + e1 * F(sv.z);
#pragma unroll
                for (int j = 16; j > 0; j >>= 1) lg += shx(lg, j);
                sts32(sbase + OFF_SC + 4 * lane, __float_as_uint(__fdividef(fmaxf(e0, e1), lg)));
                mbar_arrive(bars + 8 * B_W);
            }
            return;
        }
        const uint32_t total = roleA ? (me >= 24 ? A_END : A_W2) : P_END;
        const uint32_t tp = t0 + ((me * T_PH) >> 6);
#pragma unroll 1
        for (uint32_t i = roleA ? k : (k == 2 ? 8 : 9 + k); i < total; i += 3) {
            if (roleA && !ffn && i >= A_W1 && i < A_W2) continue;
            const uint4 e = prm.tile[roleA][i];
            const uint32_t blk = (int)(short)e.z + (e.w & 255u) * id + ((e.w >> 8) & 255u) * r;
            const uint32_t row = (e.z >> 16) + 32 * (((e.w >> 16) & 255u) * id + ((int)e.w >> 24) * r);
            if (!roleA && i >= CAP) mbar_wait(tb + 8 * (i - CAP));
            if (!roleA && i - P_WO < 3) {
                asm volatile("barrier.cluster.wait.aligned;" ::: "memory");
                mbar_wait(bars + 8 * B_EX0);
            }
            if (lane == 0) expect_tx(tb + 8 * i, (e.x >> 24) << 10);
            while ((int)(now_ns() - tp) < (int)e.y) { __nanosleep(40); }
            if (lane == 0) {
                asm volatile("cp.async.bulk.tensor.3d.shared::cluster.global.mbarrier::complete_tx::bytes [%0], [%1, {%5, %2, %3}], [%4];"
                             :: "r"(sbase + (e.x & 0xfffffu)), "l"(mapbase + 128 * ((e.x >> 20) & 7u)), "r"(row), "r"(blk), "r"(tb + 8 * i), "r"(0) : "memory");
            }
            __syncwarp();
        }
        return;
    }

    asm volatile("setmaxnreg.inc.sync.aligned.u32 112;");
    const uint32_t epoch = ld_word(scr + G_EPOCH);
    asm volatile("barrier.cluster.arrive.relaxed.aligned;" ::: "memory");
    asm volatile("barrier.cluster.wait.aligned;" ::: "memory");
    const uint32_t tag = opq((epoch & 1u) ^ 1u);
    const uint32_t g = lane >> 2, tq = lane & 3, wg = warp >> 2;
    const uint32_t tsw = opq(sbase + ((lane & 7) + (lane >> 4) * 8) * 128 + (((2 * (warp & 3) + ((lane >> 3) & 1)) ^ (lane & 7)) << 4));
    const uint32_t nsw = opq(sbase + (warp >> 1) * 8192 + (16 * (warp & 1) + (lane & 15)) * 128 + (((lane >> 4) ^ (lane & 7)) << 4));
    const uint32_t vsw = opq(sbase + (lane >> 3) * 16);
    float d[16];

    if (roleA) {
        const uint32_t xo = opq(G_X2 + (2 * ((t & 127) >> 3) + r) * 16384 + id * 512 + wg * 128 + (lane & 7) * 16);
        const uint32_t oa = opq(sbase + OFF_OT + ((lane & 7) + (lane >> 4) * 8) * 528 + warp * 32 + ((lane >> 3) & 1) * 16);
        const uint32_t ob = opq(sbase + OFF_OT + ((t & 127) >> 3) * 528 + wg * 128 + (lane & 7) * 16);
        const uint32_t pa = opq(tsw + OFF_C + (wg >> 1) * 32768 + (wg & 1) * 4096);
        if (ffn && warp == 0) st_word(scr + (G_XH + me * 128 + lane * 4), tag ^ 1u);
        wait_until(t0 + T_PW + 40 * warp);
        st_pkt2(scr + xo, make_uint4(tag ^ 1u, 0u, tag ^ 1u, 0u));
        st_pkt2(scr + xo + 32 * 16384, make_uint4(tag ^ 1u, 0u, tag ^ 1u, 0u));
        uint32_t fa[64];
        float d2[16];
        if (warp < 8) {
            const uint32_t so = sbase + OFF_SREM + (t & 127) * 16;
            const uint32_t sx = opq(wg ? so : peer_addr(so, r ^ 1));
            zero<16>(d);
#pragma unroll
            for (int cp = 1; cp >= 0; --cp) {
                mbar_wait(tb + 8 * (A_C + 4 * (1 - cp)) + 8 * (warp >> 1));
#pragma unroll
                for (int k = 0; k < 8; ++k) ldsm4(fa + 32 * cp + 4 * k, (nsw ^ ((k & 3) << 5)) + OFF_C + cp * 32768 + (k >> 2) * 4096);
            }
            if (wg) mbar_wait4(tb + 8 * (A_C + 4));
            bar_sync(BAR_Q + wg, 416);
            if (wg) { const uint32_t c = clock(); while ((uint32_t)clock() - c < (uint32_t)T_SKEW) { } }
            wg_fence();
#pragma unroll
            for (int ks = 0; ks < 16; ++ks) wgmma_rs(d, fa + 4 * ks, sdesc(sbase + OFF_Q) + (ks >> 2) * 256 + (ks & 3) * 2);
            wg_commit();
            wg_wait();
            if (wg == 0) {
                const uint32_t rbar = peer_addr(bars + 8 * B_EX0, r ^ 1);
#pragma unroll
                for (int i = 0; i < 2; ++i)
                    asm volatile("st.async.shared::cluster.mbarrier::complete_tx::bytes.v4.b32 [%0], {%1,%2,%3,%4}, [%5];"
                                 :: "r"(sx + i * 2048), "r"(pack_bf(d[8 * i], d[8 * i + 1])), "r"(pack_bf(d[8 * i + 2], d[8 * i + 3])),
                                    "r"(pack_bf(d[8 * i + 4], d[8 * i + 5])), "r"(pack_bf(d[8 * i + 6], d[8 * i + 7])), "r"(rbar) : "memory");
            }
            d2[0] = F(sx);
        } else {
            const uint32_t hq = 4 * (warp - 8) + (lane >> 3);
            const char* src = scr + opq(G_X1 + (2 * hq + r) * 512 + (lane & 7) * 16);
            const uint32_t qa = opq(sbase + OFF_Q + hq * 128 + (((lane ^ hq) & 7) << 4));
            uint4 v[4];
            wait_until(t0 + T_Q0);
#pragma unroll
            for (int k = 0; k < 3; ++k) v[k] = ld_pkt2(src + 128 * k);
            wait_until(t0 + T_Q);
            v[3] = ld_pkt2(src + 384);
#pragma unroll 1
            for (int it = 0; it < SPIN_MAX; ++it) {
                uint32_t old = 0;
#pragma unroll
                for (int k = 0; k < 4; ++k) {
                    const uint4 c = make_uint4(v[k].x ^ tag, v[k].y, v[k].z ^ tag, v[k].w);
                    old |= ((c.x | c.z) & 1u) << k;
                    sts128(qa + k * 4096, c);
                }
                if (!__any_sync(FULL, old)) break;
#pragma unroll
                for (int k = 0; k < 4; ++k) if (old >> k & 1u) v[k] = ld_pkt2(src + 128 * k);
            }
            fence_async();
            bar_arrive(BAR_Q, 416);
            bar_arrive(BAR_Q + 1, 416);
        }
        if (wg != 1) mbar_wait4(tb + 8 * A_C + 16 * (~wg & 2));
#pragma unroll
        for (int ks = 0; ks < 8; ++ks) ldsm4t(fa + 4 * ks, pa + (ks >> 1) * 8192 + (ks & 1) * 2048);
        if (wg == 1) {
            const uint32_t sx = __float_as_uint(d2[0]);
            const bool b4 = lane & 16, b3 = lane & 8, b2 = lane & 4;
            const uint32_t ha = sbase + 4 * (8 * (g >> 1) + 2 * tq + (g & 1));
            float u[8];
            uint32_t pk[8];
            mbar_wait(bars + 8 * B_EX0);
#pragma unroll
            for (int i = 0; i < 2; ++i) {
                const uint4 o = lds128(sx + i * 2048);
                d[8 * i] += bf_lo(o.x); d[8 * i + 1] += bf_hi(o.x); d[8 * i + 2] += bf_lo(o.y); d[8 * i + 3] += bf_hi(o.y);
                d[8 * i + 4] += bf_lo(o.z); d[8 * i + 5] += bf_hi(o.z); d[8 * i + 6] += bf_lo(o.w); d[8 * i + 7] += bf_hi(o.w);
            }
#pragma unroll
            for (int i = 0; i < 8; ++i) u[i] = fmaxf(d[4 * (i >> 1) + (i & 1)], d[4 * (i >> 1) + (i & 1) + 2]);
#pragma unroll
            for (int i = 0; i < 4; ++i) u[i] = fmaxf(b4 ? u[i + 4] : u[i], shx(b4 ? u[i] : u[i + 4], 16));
#pragma unroll
            for (int i = 0; i < 2; ++i) u[i] = fmaxf(b3 ? u[i + 2] : u[i], shx(b3 ? u[i] : u[i + 2], 8));
            asm volatile("red.shared.max.s32 [%0], %1;" :: "r"(ha + OFF_POWN + 4096),
                         "r"(f2ord(__float_as_int(fmaxf(b2 ? u[1] : u[0], shx(b2 ? u[0] : u[1], 4))))) : "memory");
            bar_sync(BAR_MAX, 160);
#pragma unroll
            for (int j = 0; j < 4; ++j) {
                const uint2 mi = lds64(sbase + OFF_POWN + 4096 + 32 * j + 8 * tq);
                const float m0 = ord2f((int)mi.x), m1 = ord2f((int)mi.y);
                pk[2 * j] = pack_bf(ex2(d[4 * j] - m0), ex2(d[4 * j + 1] - m1));
                pk[2 * j + 1] = pack_bf(ex2(d[4 * j + 2] - m0), ex2(d[4 * j + 3] - m1));
            }
            stsm4t(tsw + OFF_POWN, pk);
            stsm4t(tsw + OFF_POWN + 2048, pk + 4);
            fence_async();
            bar_arrive(BAR_ALL, NCOMP + 32);
            const uint32_t hm = lds32(sbase + OFF_EX0 + 8);
#pragma unroll
            for (int j = 0; j < 4; ++j) {
                u[2 * j] = F((pk[2 * j] << 16) & hm) + bf_lo(pk[2 * j + 1]);
                u[2 * j + 1] = F(pk[2 * j] & hm) + bf_hi(pk[2 * j + 1]);
            }
#pragma unroll
            for (int i = 0; i < 4; ++i) u[i] = (b4 ? u[i + 4] : u[i]) + shx(b4 ? u[i] : u[i + 4], 16);
#pragma unroll
            for (int i = 0; i < 2; ++i) u[i] = (b3 ? u[i + 2] : u[i]) + shx(b3 ? u[i] : u[i + 2], 8);
            sts32(ha + OFF_LSUM + (warp & 3) * 128, __float_as_uint((b2 ? u[1] : u[0]) + shx(b2 ? u[0] : u[1], 4)));
            bar_arrive(BAR_L, 160);
        }
        zero<16>(d); zero<16>(d2);
        bar_sync(wg == 1 ? BAR_WG + 1 : BAR_ALL, wg == 1 ? 128 : NCOMP + 32);
        wg_fence();
#pragma unroll
        for (int ks = 0; ks < 4; ++ks) wgmma_rs(d, fa + 16 + 4 * ks, sdesc(sbase + OFF_POWN) + ks * 2);
        mbar_wait2(bars + 8 * B_EX2, bars + 8 * B_W);
        wg_fence();
#pragma unroll
        for (int ks = 0; ks < 4; ++ks) wgmma_rs(d2, fa + 4 * ks, sdesc(sbase + OFF_PIN) + ks * 2);
        wg_commit();
        {
            uint4 ab[4];
            uint32_t ok[8];
#pragma unroll
            for (int j = 0; j < 4; ++j) ab[j] = lds128(sbase + OFF_SC + 64 * j + 16 * tq);
            wg_wait();
#pragma unroll
            for (int i = 0; i < 8; ++i)
                ok[i] = pack_bf(F(ab[i >> 1].x) * d[2 * i] + F(ab[i >> 1].y) * d2[2 * i], F(ab[i >> 1].z) * d[2 * i + 1] + F(ab[i >> 1].w) * d2[2 * i + 1]);
            stsm4t(oa, ok);
            stsm4t(oa + 16 * 528, ok + 4);
            bar_sync(BAR_WG + wg, 128);
#pragma unroll
            for (int i = 0; i < 2; ++i) {
                uint4 v = lds128(ob + i * 16 * 528);
                v.x = tag_word(v.x, tag); v.z = tag_word(v.z, tag);
                st_pkt2(scr + xo + i * (32 * 16384), v);
            }
        }
        if (ffn) {
            uint32_t a[20], b[12];
            const uint32_t xa = vsw + OFF_XS + 640 * r + wg * 160;
            ldsm4(b, xa); ldsm4(b + 4, xa + 64); ldsm4(b + 8, xa + 128);
            mbar_wait2(tb + 8 * A_W1 + 8 * wg, tb + 8 * (A_W1 + 1) + 8 * wg);
#pragma unroll
            for (int k = 0; k < 5; ++k) ldsm4t(a + 4 * k, tsw + OFF_W1 + wg * 10240 + k * 2048);
            zero<8>(d);
#pragma unroll
            for (int k = 0; k < 5; ++k) mma_w(d + 4 * (k & 1), a + 4 * k, b[2 * k], b[2 * k + 1]);
            const uint32_t rank = (warp >> 1) & 1;
            if (tq < 2)
                st_async(peer_addr(sbase + OFF_EX1 + ((4 * r + wg) * 32 + 16 * (warp & 1) + g + 8 * tq) * 4, rank),
                         __float_as_uint(tq ? d[2] + d[6] : d[0] + d[4]), peer_addr(bars + 8 * B_EX1, rank));
            if (warp == 0) {
                mbar_wait(bars + 8 * B_EX1);
                float h = 0.f;
#pragma unroll
                for (int i = 0; i < 8; ++i) h += ldsf(sbase + OFF_EX1 + lane * 4 + 128 * i);
                h = bf_round(h);
                st_word(scr + (G_XH + me * 128 + lane * 4), __float_as_uint(bf_round(__fdividef(h, 1.0f + __expf(-h)))) | tag);
            }
        }
        if (me >= 24) {
            const float gg = ldsf(sbase + OFF_EX0 + (warp >> 3) * 4);
            if (warp < 8) {
                const char* rsrc = scr + opq(G_X4 + (me - 24) * 4096 + t * 16);
                const uint32_t rw = opq(sbase + OFF_O + (warp * 16 + 4 * tq + (lane >> 3)) * 4);
                wait_until(t0 + T_R);
                const uint4 rv = poll_word4(rsrc, tag, true);
                const bool b4 = lane & 16, b3 = lane & 8;
                const float y0 = F(b4 ? rv.z : rv.x) + shx(F(b4 ? rv.x : rv.z), 16), y1 = F(b4 ? rv.w : rv.y) + shx(F(b4 ? rv.y : rv.w), 16);
                float y = (b3 ? y1 : y0) + shx(b3 ? y0 : y1, 8);
                y += shx(y, 4);
                sts32(rw, __float_as_uint(gg * y));
            } else {
                const uint32_t w8 = warp - 8, wrow = 16 * w8 + (lane & 7) + (lane >> 4) * 8;
                const uint32_t wa = opq(sbase + OFF_W2 + wrow * 64 + ((((lane >> 3) & 1) ^ ((wrow >> 1) & 3)) << 4));
                const uint32_t rw = opq(peer_addr(sbase + OFF_O + (((tq >> 1) == r ? warp : warp + 8) * 16 + g + 8 * (tq & 1)) * 4, tq >> 1));
                wait_until(t0 + T_H);
                const uint4 hv = poll_word4(scr + (G_XH + (864 * r + 128 * g + 16 * w8 + 4 * tq) * 4), tag, 128 * g + 16 * w8 < 864);
                sts64(sbase + OFF_Q + w8 * 256 + lane * 8, __byte_perm(hv.x, hv.y, 0x7632), __byte_perm(hv.z, hv.w, 0x7632));
                __syncwarp();
                uint32_t b[16];
#pragma unroll
                for (int j = 0; j < 4; ++j) ldsm4(b + 4 * j, vsw + OFF_Q + w8 * 256 + j * 64);
                zero<16>(d);
#pragma unroll
                for (int jj = 0; jj < 3; ++jj) {
                    uint32_t a[24];
                    mbar_wait2(tb + 8 * (A_W2 + 2 * jj), tb + 8 * (A_W2 + 2 * jj + 1));
#pragma unroll
                    for (int k = 0; k < 4; ++k) ldsm4t(a + 4 * k, (wa ^ ((k & 1) << 5)) + (2 * jj + (k >> 1)) * 8192);
                    if (jj == 2 && w8 < 6) { ldsm4t(a + 16, wa + 6 * 8192); ldsm4t(a + 20, (wa ^ 32) + 6 * 8192); }
#pragma unroll
                    for (int k = 0; k < 4; ++k) mma_w(d + 4 * k, a + 4 * k, b[4 * jj + 2 * (k >> 1)], b[4 * jj + 2 * (k >> 1) + 1]);
                    if (jj == 2 && w8 < 6) { mma_w(d, a + 16, b[12], b[13]); mma_w(d + 4, a + 20, b[12], b[13]); }
                }
                const float o = gg * (tq == 0 ? d[0] + d[8] : (tq == 1 ? d[2] + d[10] : (tq == 2 ? d[4] + d[12] : d[6] + d[14])));
                if ((tq >> 1) == r) asm volatile("st.shared::cluster.f32 [%0], %1;" :: "r"(rw), "f"(o) : "memory");
                else st_async(rw, __float_as_uint(o), peer_addr(bars + 8 * B_R, r ^ 1));
            }
            if (warp != 15) bar_arrive(BAR_Q, NCOMP);
            else {
                const uint32_t rp = opq(sbase + OFF_O + ((lane >> 4) * 192 + (lane & 15)) * 4);
                char* const op = reinterpret_cast<char*>(prm.out) + opq(32 * (me - 24) + 2 * lane);
                mbar_wait(bars + 8 * B_R);
                bar_sync(BAR_Q, NCOMP);
                float z = 0.f, z1 = 0.f, z2 = 0.f;
#pragma unroll
                for (int i = 0; i < 4; ++i) { z += ldsf(rp + 192 * i); z1 += ldsf(rp + 192 * i + 64); z2 += ldsf(rp + 192 * i + 128); }
                z += z1 + z2;
                z += shx(z, 16);
                if (lane < 16) *reinterpret_cast<__nv_bfloat16*>(op) = __float2bfloat16_rn(z);
                if (me == 24 && lane == 0) st_word(scr + G_EPOCH, epoch + 1u);
            }
        }
    } else {
        asm volatile("cp.async.mbarrier.arrive.noinc.shared::cta.b64 [%0];" :: "r"(tb + 8 * wg) : "memory");
        asm volatile("cp.async.mbarrier.arrive.noinc.shared::cta.b64 [%0];" :: "r"(tb + 8 * wg + 32) : "memory");
        const uint32_t oo = opq(G_X4 + (warp + 16 * (tq >> 1)) * 4096 + me * 64 + (g + 8 * (tq & 1)) * 4);
        const uint32_t qo = opq(G_X1 + me * 512 + (4 * warp + 2 * tq + (lane >> 4)) * 8);
        if ((lane & 14) == 0) st_pkt(scr + qo, tag ^ 1u, 0u);
        st_word(scr + oo, tag ^ 1u);
        if (tq < 2 && warp < 8) st_word(scr + oo + 32 * 4096, tag ^ 1u);
        uint32_t a[32], b[16];
        if (warp < 8) {
            const uint32_t rdst = opq(peer_addr(sbase + OFF_EX0 + (r * 128 + 16 * warp + g + 8 * (tq & 1)) * 4, tq >> 1));
            mbar_wait(bars + 8 * B_X);
            zero<8>(d);
#pragma unroll 1
            for (int kb = 0; kb < 10; ++kb) {
                ldsm4(b, vsw + OFF_XS + 640 * r + 64 * kb);
                mbar_wait(tb + 8 * (P_WQ + kb));
                ldsm4t(a, tsw + OFF_WO + wg * 4096 + kb * 8192); ldsm4t(a + 4, tsw + OFF_WO + 2048 + wg * 4096 + kb * 8192);
                mma_w(d, a, b[0], b[1]); mma_w(d + 4, a + 4, b[2], b[3]);
            }
            st_async(rdst, __float_as_uint((tq & 1) ? d[2] + d[6] : d[0] + d[4]), peer_addr(bars + 8 * B_EX0, tq >> 1));
        }
        {
            mbar_wait(bars + 8 * B_EX0);
            const uint4 q0 = lds128(sbase + OFF_EX0 + lane * 16), q1 = lds128(sbase + OFF_EX0 + 512 + lane * 16);
            sts64(sbase + OFF_O + lane * 8, pack_bf(F(q0.x) + F(q1.x), F(q0.y) + F(q1.y)), pack_bf(F(q0.z) + F(q1.z), F(q0.w) + F(q1.w)));
            __syncwarp();
#pragma unroll
            for (int k = 0; k < 4; ++k) ldsm4(b + 4 * k, vsw + OFF_O + 64 * k);
            zero<16>(d);
            mbar_wait(tb + 8 * P_WUK + 8 * (warp >> 1));
#pragma unroll
            for (int k = 0; k < 8; ++k) ldsm4(a + 4 * k, (nsw ^ ((k & 3) << 5)) + OFF_WUK + (k >> 2) * 4096);
#pragma unroll
            for (int k = 0; k < 8; ++k) mma_w(d + 4 * (k & 3), a + 4 * k, b[2 * k], b[2 * k + 1]);
            const float sc = 0.08838834764831845f * 1.4426950408889634f;
            const float v = ((tq & 1) ? (d[2] + d[6]) + (d[10] + d[14]) : (d[0] + d[4]) + (d[8] + d[12])) * sc;
            const uint32_t w = pack_bf(v, __shfl_down_sync(FULL, v, 4));
            const uint32_t w2 = __shfl_down_sync(FULL, w, 8);
            if ((lane & 14) == 0) st_pkt(scr + qo, tag_word(w, tag), w2);
        }
        const uint32_t rank = wg & 1;
        const char* src = scr + opq(G_X2 + me * 16384 + (warp >> 1) * 2048 + (warp & 1) * 256 + lane * 8);
        const uint32_t rdst = opq(peer_addr(sbase + OFF_EX1 + (2 * r + (warp >> 3)) * 144 + (16 * (warp & 3) + g + 8 * (tq & 1)) * 2, rank));
        const uint32_t rbar = opq(peer_addr(bars + 8 * B_EX1, rank));
        const uint32_t ow = opq(sbase + OFF_O + (warp >> 1) * 528 + (warp & 1) * 256 + lane * 8);
        const uint32_t ol = opq(vsw + OFF_O + (lane & 7) * 528 + (warp >> 3) * 256);
        const uint32_t cl = opq(vsw + OFF_EX1 + (lane & 3) * 144);
        const uint32_t wm = opq(tsw + OFF_WO + (warp >> 3) * 16384 + rank * 4096), ob = tb + 8 * P_WO + 16 * (warp >> 3);
        mbar_wait4(tb + 8 * P_WUV + 32 * (warp >> 3));
#pragma unroll
        for (int k = 0; k < 8; ++k) ldsm4t(a + 4 * k, tsw + OFF_WUV + (warp >> 3) * 32768 + rank * 4096 + (k >> 1) * 8192 + (k & 1) * 2048);
        zero<16>(d);
        mbar_wait(bars + 8 * B_EX2);
        wait_until(lds32(sbase + OFF_LSUM));
        uint2 v[4];
#pragma unroll
        for (int i = 0; i < 4; ++i) v[i] = ld_pkt(src + 512 * i);
        uint32_t w0[16];
#define LOAD_WO(dst_, i_) do { _Pragma("unroll") for (int k = 0; k < 4; ++k) ldsm4t((dst_) + 4 * k, wm + (i_) * 32768 + (k >> 1) * 8192 + (k & 1) * 2048); } while (0)
        const bool early = mbar_test2(ob);
        if (early) LOAD_WO(w0, 0);
        mbar_wait(bars + 8 * B_W);
        const uint4 wn = lds128(sbase + OFF_SC + 16 * (warp >> 1));
#pragma unroll 1
        for (int it = 0; it < SPIN_MAX; ++it) {
#pragma unroll
            for (int i = 0; i < 4; ++i) v[i].x ^= tag;
            if (!stale(v[0].x | v[1].x | v[2].x | v[3].x)) break;
#pragma unroll
            for (int i = 0; i < 4; ++i) v[i] = ld_pkt(src + 512 * i);
        }
#define MRG(f, h) (F(wn.x) * h(v[0].f) + F(wn.y) * h(v[1].f) + F(wn.z) * h(v[2].f) + F(wn.w) * h(v[3].f))
        sts64(ow, pack_bf(MRG(x, bf_lo), MRG(x, bf_hi)), pack_bf(MRG(y, bf_lo), MRG(y, bf_hi)));
        bar_sync(BAR_ALL, NCOMP);
#pragma unroll
        for (int k = 0; k < 4; ++k) ldsm4(b + 4 * k, ol + 64 * k);
#pragma unroll
        for (int k = 0; k < 8; ++k) mma_w(d + 4 * (k & 3), a + 4 * k, b[2 * k], b[2 * k + 1]);
        {
            const float c0 = ((d[0] + d[1]) + (d[4] + d[5])) + ((d[8] + d[9]) + (d[12] + d[13]));
            const float c1 = ((d[2] + d[3]) + (d[6] + d[7])) + ((d[10] + d[11]) + (d[14] + d[15]));
            float c = ((tq & 1) ? c1 : c0) + shx((tq & 1) ? c0 : c1, 1);
            c += shx(c, 2);
            const uint32_t cw = pack_bf(c, __shfl_down_sync(FULL, c, 4));
            if ((lane & 6) == 0) st_async(rdst, cw, rbar);
        }
        if (!early) { mbar_wait2(ob, ob + 8); LOAD_WO(w0, 0); }
        mbar_wait2(ob + 32, ob + 40);
        LOAD_WO(a, 1);
        const bool third = warp < 8 && mbar_test2(ob + 64);
        if (third) LOAD_WO(a + 16, 2);
        zero<16>(d);
        mbar_wait(bars + 8 * B_EX1);
        ldsm4(b, cl); ldsm4(b + 4, cl + 64);
#pragma unroll
        for (int k = 0; k < 4; ++k) {
            mma_w(d + 4 * (k & 1), w0 + 4 * k, b[2 * k], b[2 * k + 1]);
            mma_w(d + 8 + 4 * (k & 1), a + 4 * k, b[2 * k], b[2 * k + 1]);
        }
        {
            const float lo = tq < 2 ? (d[0] + d[1]) + (d[4] + d[5]) : (d[8] + d[9]) + (d[12] + d[13]);
            const float hi = tq < 2 ? (d[2] + d[3]) + (d[6] + d[7]) : (d[10] + d[11]) + (d[14] + d[15]);
            st_word(scr + oo, tag_word(__float_as_uint(((tq & 1) ? hi : lo) + shx((tq & 1) ? lo : hi, 1)), tag));
        }
        if (warp < 8) {
            if (!third) { mbar_wait2(ob + 64, ob + 72); LOAD_WO(a + 16, 2); }
            zero<16>(d);
#pragma unroll
            for (int k = 0; k < 4; ++k) mma_w(d + 4 * k, a + 16 + 4 * k, b[2 * k], b[2 * k + 1]);
            const float lo = ((d[0] + d[1]) + (d[4] + d[5])) + ((d[8] + d[9]) + (d[12] + d[13]));
            const float hi = ((d[2] + d[3]) + (d[6] + d[7])) + ((d[10] + d[11]) + (d[14] + d[15]));
            const float o = ((tq & 1) ? hi : lo) + shx((tq & 1) ? lo : hi, 1);
            if (tq < 2) st_word(scr + oo + 32 * 4096, tag_word(__float_as_uint(o), tag));
        }
    }
}

typedef const __nv_bfloat16* BP;
__device__ float f_q[4096], f_qa[32 * DC], f_p[32 * SK], f_lat[32 * DC], f_ctx[4096], f_h[FF];
DEVI float bf(BP p, size_t i) { return __bfloat162float(p[i]); }
__global__ void fb_in(BP x, BP wq, BP w1) {
    const int n = blockIdx.x * blockDim.x + threadIdx.x;
    if (n >= 4096 + FF) return;
    float s = 0.f;
    for (int m = 0; m < MD; ++m) s += bf(x, m) * (n < 4096 ? bf(wq, (size_t)m * 4096 + n) : bf(w1, (size_t)m * FF + n - 4096));
    s = bf_round(s);
    if (n < 4096) f_q[n] = s; else f_h[n - 4096] = bf_round(s / (1.0f + expf(-s)));
}
__global__ void fb_qabs(BP wuk) {
    const int n = blockIdx.x * blockDim.x + threadIdx.x, h = n / DC, c = n % DC;
    float s = 0.f;
    for (int k = 0; k < 128; ++k) s += bf(wuk, ((size_t)c * 32 + h) * 128 + k) * f_q[h * 128 + k];
    f_qa[n] = s * 0.08838834764831845f;
}
__global__ void fb_attn(BP ckv) {
    __shared__ float red[512];
    const int h = blockIdx.x, t = threadIdx.x;
    float m = -INFINITY;
    for (int k = t; k < SK; k += 512) {
        float s = 0.f;
        for (int c = 0; c < DC; ++c) s += bf(ckv, (size_t)k * DC + c) * f_qa[h * DC + c];
        f_p[h * SK + k] = s; m = fmaxf(m, s);
    }
    red[t] = m; __syncthreads();
    for (int i = 0; i < 512; ++i) m = fmaxf(m, red[i]);
    __syncthreads();
    float l = 0.f;
    for (int k = t; k < SK; k += 512) { const float e = expf(f_p[h * SK + k] - m); f_p[h * SK + k] = e; l += e; }
    red[t] = l; __syncthreads();
    l = 0.f;
    for (int i = 0; i < 512; ++i) l += red[i];
    float a = 0.f;
    for (int k = 0; k < SK; ++k) a += f_p[h * SK + k] * bf(ckv, (size_t)k * DC + t);
    f_lat[h * DC + t] = a / l;
}
__global__ void fb_ctx(BP wuv) {
    const int n = blockIdx.x * blockDim.x + threadIdx.x;
    float s = 0.f;
    for (int c = 0; c < DC; ++c) s += f_lat[(n >> 7) * DC + c] * bf(wuv, (size_t)c * 4096 + n);
    f_ctx[n] = bf_round(s);
}
__global__ void fb_out(BP x, BP gw, BP wo, BP w2, __nv_bfloat16* out) {
    const int n = blockIdx.x * blockDim.x + threadIdx.x;
    float s = 0.f, a = 0.f, b = 0.f;
    for (int m = 0; m < MD; ++m) s += bf_round(bf(x, m) * bf(gw, m));
    for (int k = 0; k < 4096; ++k) a += f_ctx[k] * bf(wo, (size_t)k * MD + n);
    for (int k = 0; k < FF; ++k) b += f_h[k] * bf(w2, (size_t)k * MD + n);
    const float g = bf_round(1.0f / (1.0f + expf(-bf_round(s))));
    out[n] = __float2bfloat16_rn(g * a + bf_round(1.0f - g) * b);
}

typedef CUresult (*EncodeFn)(CUtensorMap*, CUtensorMapDataType, cuuint32_t, void*, const cuuint64_t*, const cuuint64_t*,
                             const cuuint32_t*, const cuuint32_t*, CUtensorMapInterleave, CUtensorMapSwizzle,
                             CUtensorMapL2promotion, CUtensorMapFloatOOBfill);

void make_map(EncodeFn enc, CUtensorMap* m, void* base, uint64_t cols, uint64_t rows, uint32_t brows, uint32_t bblk, uint32_t bw = 64) {
    cuuint64_t dims[3] = {bw, rows, cols / bw};
    cuuint64_t strides[2] = {cols * 2, bw * 2};
    cuuint32_t box[3] = {bw, brows, bblk};
    cuuint32_t es[3] = {1, 1, 1};
    enc(m, CU_TENSOR_MAP_DATA_TYPE_BFLOAT16, 3, base, dims, strides, box, es, CU_TENSOR_MAP_INTERLEAVE_NONE,
        bw == 64 ? CU_TENSOR_MAP_SWIZZLE_128B : CU_TENSOR_MAP_SWIZZLE_64B, CU_TENSOR_MAP_L2_PROMOTION_NONE, CU_TENSOR_MAP_FLOAT_OOB_FILL_NONE);
}

}

extern "C" void kernel_launch(void* const* d_in, const int* in_sizes, int n_in, void* d_out, int out_size) {
    (void)in_sizes; (void)n_in; (void)out_size;
    static EncodeFn enc = nullptr;
    static void* scr = nullptr;
    static int mode = 0;
    if (!mode) {
        cudaFuncSetAttribute(fused_kernel, cudaFuncAttributeMaxDynamicSharedMemorySize, SMEM_BYTES);
        cudaGetSymbolAddress(&scr, g_scr);
        void* fn = nullptr;
        cudaDriverEntryPointQueryResult qr;
        cudaGetDriverEntryPoint("cuTensorMapEncodeTiled", &fn, cudaEnableDefault, &qr);
        enc = (EncodeFn)fn;
        cudaLaunchConfig_t cfg = {};
        cudaLaunchAttribute at;
        at.id = cudaLaunchAttributeClusterDimension;
        at.val.clusterDim.x = 2; at.val.clusterDim.y = 1; at.val.clusterDim.z = 1;
        cfg.gridDim = dim3(NCTA); cfg.blockDim = dim3(NTHREADS); cfg.dynamicSmemBytes = SMEM_BYTES; cfg.attrs = &at; cfg.numAttrs = 1;
        int nclusters = 0;
        const cudaError_t e = cudaOccupancyMaxActiveClusters(&nclusters, fused_kernel, &cfg);
        (void)cudaGetLastError();
        mode = (enc && e == cudaSuccess && nclusters >= NCTA / 2) ? 1 : 2;
    }
    if (mode == 2) {
        fb_in<<<(4096 + FF + 63) / 64, 64>>>((BP)d_in[0], (BP)d_in[2], (BP)d_in[7]);
        fb_qabs<<<32 * DC / 128, 128>>>((BP)d_in[3]);
        fb_attn<<<32, 512>>>((BP)d_in[1]);
        fb_ctx<<<4096 / 64, 64>>>((BP)d_in[4]);
        fb_out<<<MD / 32, 32>>>((BP)d_in[0], (BP)d_in[9], (BP)d_in[5], (BP)d_in[8], (__nv_bfloat16*)d_out);
        return;
    }
    Params prm;
    prm.x = (const __nv_bfloat16*)d_in[0];
    prm.gw = (const __nv_bfloat16*)d_in[9];
    prm.out = (__nv_bfloat16*)d_out;
    const int TP1 = 2250, DD1 = 180;
    const int TA1 = 2580, DA1 = 140;
    const int T3 = 4030, DP2 = 232, DA2 = 395, DP3 = 180;
    const int TW2 = 7640, DW2 = 95;
    for (int i = 0; i < 36; ++i) {
        auto mk = [](int dst, int map, int kb, int when, int blk, int row, int blki, int blkr, int rowi, int rowr) {
            return make_uint4(dst | map << 20 | kb << 24, when, (blk & 0xffff) | row << 16, blki | blkr << 8 | rowi / 32 << 16 | (unsigned)(rowr / 32) << 24);
        };
        const int j = i - P_WO, f = i - A_W2;
        prm.tile[0][i] = i < P_WUK ? mk(OFF_WO + i * 8192, 0, 8, TP1 + (i - 17) * DD1, 0, 32 * i, 2, 0, 0, 320)
                       : i < P_WUV ? mk(OFF_WUK + (i - P_WUK) * 8192, 1, 8, TP1 + (i - 17) * DD1, 0, 32 * (i - P_WUK), 2, 0, 0, 256)
                       : i < P_WO  ? mk(OFF_WUV + (i - P_WUV) * 8192, 2, 8, T3 + (i - P_WUV) * DP2, 0, 32 * (i - P_WUV), 2, 0, 0, 256)
                                   : mk(OFF_WO + j * 8192, 3, 8, T3 + 8 * DP2 + j * DP3, j & ~1, 32 * (j & 1), 0, 0, 128, 64);
        prm.tile[1][i] = i < A_W1 ? mk(OFF_C + ((i ^ 4) & 7) * 8192, 4, 8, TA1 + i * DA1, i < 4 ? 2 : 0, 32 * ((i ^ 2) & 3), 0, 4, 128, (i & 2) ? 64 : -64)
                       : i < A_W2 ? mk(OFF_W1 + (i - A_W1) * 8192, 5, 8, T3 + (i - A_W1) * DA2, 0, 64 * (i - A_W1), 1, 0, 0, 320)
                                  : mk(OFF_W2 + f * 9216, 6, 9, TW2 + f * DW2, -12, 144 * f, 1, 0, 0, 864);
    }
    make_map(enc, &prm.m[0], d_in[2], 4096, MD, 32, 2);
    make_map(enc, &prm.m[1], d_in[3], 4096, DC, 32, 2);
    make_map(enc, &prm.m[2], d_in[4], 4096, DC, 32, 2);
    make_map(enc, &prm.m[3], d_in[5], MD, 4096, 32, 2);
    make_map(enc, &prm.m[4], d_in[1], DC, SK, 32, 2);
    make_map(enc, &prm.m[5], d_in[7], FF, MD, 64, 1);
    make_map(enc, &prm.m[6], d_in[8], MD, FF, 144, 1, 32);
    fused_kernel<<<NCTA, NTHREADS, SMEM_BYTES>>>((const char*)d_in[2], (char*)scr, prm);
}
```
